```python
import torch

def _softmax(x, axis=-1):
    return torch.softmax(x, dim=axis)

def _gelu(x):
    return torch.nn.functional.gelu(x, approximate='tanh')

def _silu(x):
    return torch.nn.functional.silu(x)

def _sigmoid(x):
    return torch.sigmoid(x)

def _layernorm(x, axis=-1, eps=1e-05):
    m = x.mean(dim=axis, keepdim=True)
    v = x.var(dim=axis, keepdim=True, unbiased=False)
    return (x - m) / torch.sqrt(v + eps)

def _scatter_add(tgt, idx, src, axis=0):
    return tgt.clone().index_add_(axis, idx, src)

def _segment_sum(src, seg, n):
    out = torch.zeros((n,) + src.shape[1:], dtype=src.dtype)
    return out.index_add_(0, seg, src)

def _pad(x, pw):
    flat = tuple((v for pair in reversed(pw) for v in pair))
    return torch.nn.functional.pad(x, flat)
kernel_name = 'gated_mix__memory_aug_recurrent_mem_tr__ssm_conv_h3__prompt'

def setup_inputs():

    _w = lambda a: (lambda t: t.to(torch.bfloat16) if t.is_floating_point() else t)(torch.as_tensor(a))

    def _A_setup():
        B, S, Dm = (1, 2048, 640)
        H, Dh = (32, 128)
        M, seg = (8, 32)
        seg = min(seg, S)
        S = S // seg * seg
        return {'x': _w((lambda *s: torch.randn(*s, dtype=torch.bfloat16) * 0.05)(B, S, Dm)), 'mem0': _w((lambda *s: torch.randn(*s, dtype=torch.bfloat16) * 0.4)(B, M, Dm)), 'Wq': _w((lambda *s: torch.randn(*s, dtype=torch.bfloat16) * 6.4)(Dm, H, Dh) * Dm ** (-0.5)), 'Wk': _w((lambda *s: torch.randn(*s, dtype=torch.bfloat16) * 6.4)(Dm, H, Dh) * Dm ** (-0.5)), 'Wv': _w((lambda *s: torch.randn(*s, dtype=torch.bfloat16) * 0.4)(Dm, H, Dh) * Dm ** (-0.5)), 'Wo': _w((lambda *s: torch.randn(*s, dtype=torch.bfloat16) * 0.4)(H, Dh, Dm) * (H * Dh) ** (-0.5)), 'seg_len': seg}
    _A_in = _A_setup()

    def _B_setup():
        B, S, D = (1, 2048, 640)
        ks = 4
        return {'q': _w((lambda *s: torch.randn(*s, dtype=torch.bfloat16) * 0.05)(B, S, D)), 'k': _w((lambda *s: torch.randn(*s, dtype=torch.bfloat16) * 0.4)(B, S, D)), 'v': _w((lambda *s: torch.randn(*s, dtype=torch.bfloat16) * 0.4)(B, S, D)), 'shift_k': _w((lambda *s: torch.randn(*s, dtype=torch.bfloat16) * 0.4)(D, ks) * 0.5), 'ssm_k': _w((lambda *s: torch.randn(*s, dtype=torch.bfloat16) * 0.4)(D, S) * (1.0 / S ** 0.5)), 'ssm_D': _w((lambda *s: torch.randn(*s, dtype=torch.bfloat16) * 0.4)(D))}
    _B_in = _B_setup()
    return {'A_x': _A_in['x'], 'A_mem0': _A_in['mem0'], 'A_Wq': _A_in['Wq'], 'A_Wk': _A_in['Wk'], 'A_Wv': _A_in['Wv'], 'A_Wo': _A_in['Wo'], 'A_seg_len': _A_in['seg_len'], 'B_q': _B_in['q'], 'B_k': _B_in['k'], 'B_v': _B_in['v'], 'B_shift_k': _B_in['shift_k'], 'B_ssm_k': _B_in['ssm_k'], 'B_ssm_D': _B_in['ssm_D'], 'gate_w': _w((lambda *s: torch.randn(*s, dtype=torch.bfloat16) * 0.05)(640) * 16.0)}

def reference(A_x, A_mem0, A_Wq, A_Wk, A_Wv, A_Wo, A_seg_len, B_q, B_k, B_v, B_shift_k, B_ssm_k, B_ssm_D, gate_w):

    def _A_ref(x, mem0, Wq, Wk, Wv, Wo, seg_len):
        B, S, Dm = x.shape
        H, Dh = (Wq.shape[1], Wq.shape[2])
        M = mem0.shape[1]
        scale = Dh ** (-0.5)
        n_seg = S // seg_len
        L = M + seg_len
        idx = torch.arange(L)
        mask = (idx[:, None] < M) | (idx[:, None] >= idx[None, :])
        mem = mem0
        outs = []
        for s in range(n_seg):
            xs = x[:, s * seg_len:(s + 1) * seg_len, :].clone()
            h = torch.concatenate([mem, xs], axis=1)
            q = torch.einsum('btd,dhe->bhte', h, Wq)
            k = torch.einsum('btd,dhe->bhte', h, Wk)
            v = torch.einsum('btd,dhe->bhte', h, Wv)
            scores = torch.einsum('bhqe,bhke->bhqk', q, k) * scale
            scores = torch.where(mask[None, None], scores, -1000000000.0)
            p = _softmax(scores, axis=-1)
            o = torch.einsum('bhqk,bhke->bhqe', p, v)
            o = torch.einsum('bhte,hed->btd', o, Wo)
            mem = o[:, :M, :].clone()
            outs.append(o[:, M:, :])
        return torch.concatenate(outs, axis=1)

    def _B_ref(q, k, v, shift_k, ssm_k, ssm_D):
        B, S, D = q.shape
        ks = shift_k.shape[-1]
        k_pad = _pad(k, ((0, 0), (ks - 1, 0), (0, 0)))
        k_shift = torch.zeros_like(k)
        for t in range(ks):
            k_shift = k_shift + k_pad[:, t:t + S, :] * shift_k[:, ks - 1 - t][None, None, :]
        kv = k_shift * v
        L = 2 * S
        kv_pad = _pad(kv, ((0, 0), (0, S), (0, 0)))
        kf_pad = _pad(ssm_k, ((0, 0), (0, S)))
        kv_f = (lambda x, axes=(-2, -1): torch.fft.rfft2(x.float(), dim=axes))(kv_pad[:, None, :, :], axes=(1, 2))
        kf_f = (lambda x, axes=(-2, -1): torch.fft.rfft2(x.float(), dim=axes))(kf_pad[:, None, :], axes=(1, 2))
        kf_f = (lambda x, *d: x.permute(*d))(kf_f, 1, 2, 0)
        y_f = kv_f * kf_f[None, :, :, :]
        y = (lambda x, s, axes=(-2, -1): torch.fft.irfft2(x, s=s, dim=axes).to(torch.bfloat16))(y_f, (1, L), axes=(1, 2))[:, 0, :S, :]
        y = y + kv * ssm_D[None, None, :]
        return q * y
    x = A_x
    g = _sigmoid((x * gate_w).sum(-1, keepdims=True))
    a = _A_ref(x, A_mem0, A_Wq, A_Wk, A_Wv, A_Wo, A_seg_len)
    b = _B_ref(x, B_k, B_v, B_shift_k, B_ssm_k, B_ssm_D)
    return g * a + (1 - g) * b
```

```cpp
#include <cuda_runtime.h>
#include <cuda_bf16.h>
#include <cuda.h>
#include <stdint.h>

typedef __nv_bfloat16 bf16;
constexpr int SEQ = 2048, DM = 640, NH = 32, DH = 128, NM = 8, SEG = 32, NSEG = 64, HD = 4096;

__device__ __forceinline__ uint32_t smem_u32(const void* p) { return (uint32_t)__cvta_generic_to_shared(p); }
__device__ __forceinline__ uint32_t mapa(uint32_t a, uint32_t r) { uint32_t d; asm volatile("mapa.shared::cluster.u32 %0, %1, %2;" : "=r"(d) : "r"(a), "r"(r)); return d; }
__device__ __forceinline__ void mbar_init(uint32_t a, uint32_t c) { asm volatile("mbarrier.init.shared::cta.b64 [%0], %1;" :: "r"(a), "r"(c) : "memory"); }
__device__ __forceinline__ void mbar_expect_tx(uint32_t a, uint32_t tx) { asm volatile("mbarrier.arrive.expect_tx.shared::cta.b64 _, [%0], %1;" :: "r"(a), "r"(tx) : "memory"); }
__device__ __forceinline__ void mbar_arrive(uint32_t a) { asm volatile("mbarrier.arrive.shared::cta.b64 _, [%0];" :: "r"(a) : "memory"); }
__device__ __forceinline__ bool mbar_try(uint32_t a, uint32_t ph) {
  uint32_t ok; asm volatile("{ .reg .pred p; mbarrier.try_wait.parity.shared::cta.b64 p, [%1], %2; selp.u32 %0, 1, 0, p; }" : "=r"(ok) : "r"(a), "r"(ph) : "memory"); return ok; }
__device__ int g_err;
constexpr int SPIN_LIMIT = 1 << 21;
__device__ __forceinline__ bool give_up(int& n, int code) {
  if ((++n & 1023) != 0) return false;
  if (n > SPIN_LIMIT) *(volatile int*)&g_err = code;
  return *(volatile int*)&g_err != 0;
}
__device__ __forceinline__ int opaque_tid() { int t; asm volatile("mov.u32 %0, %%tid.x;" : "=r"(t)); return t; }
template<int ROLE = 0> __device__ __forceinline__ void mbar_wait(uint32_t a, uint32_t ph) {
  if (mbar_try(a, ph)) return;
  int n = 0; while (!mbar_try(a, ph)) { if (give_up(n, 1)) break; } }
__device__ __forceinline__ void st_async_v2(uint32_t addr, uint32_t x, uint32_t y, uint32_t mbar) {
  asm volatile("st.async.weak.shared::cluster.mbarrier::complete_tx::bytes.v2.b32 [%0], {%1,%2}, [%3];" :: "r"(addr), "r"(x), "r"(y), "r"(mbar) : "memory"); }
__device__ __forceinline__ void cluster_sync_all() { asm volatile("barrier.cluster.arrive.release.aligned; barrier.cluster.wait.acquire.aligned;" ::: "memory"); }
__device__ __forceinline__ void bar_sync(int id, int n) { asm volatile("bar.sync %0, %1;" :: "r"(id), "r"(n) : "memory"); }
__device__ __forceinline__ uint4 ld_relaxed_v4(const uint32_t* p) { uint4 v; asm volatile("ld.relaxed.gpu.global.v4.u32 {%0,%1,%2,%3}, [%4];" : "=r"(v.x), "=r"(v.y), "=r"(v.z), "=r"(v.w) : "l"(p) : "memory"); return v; }
__device__ __forceinline__ void st_relaxed_v4(uint32_t* p, uint32_t a, uint32_t b, uint32_t c, uint32_t d) { asm volatile("st.relaxed.gpu.global.v4.u32 [%0], {%1,%2,%3,%4};" :: "l"(p), "r"(a), "r"(b), "r"(c), "r"(d) : "memory"); }
__device__ __forceinline__ void st_relaxed(uint32_t* p, uint32_t v) { asm volatile("st.relaxed.gpu.global.u32 [%0], %1;" :: "l"(p), "r"(v) : "memory"); }
__device__ __forceinline__ uint32_t ld_acquire(const uint32_t* p) { uint32_t v; asm volatile("ld.acquire.gpu.global.u32 %0, [%1];" : "=r"(v) : "l"(p) : "memory"); return v; }
__device__ __forceinline__ void red_release(uint32_t* p, uint32_t v) { asm volatile("red.release.gpu.global.add.u32 [%0], %1;" :: "l"(p), "r"(v) : "memory"); }
__device__ __forceinline__ void st_release(uint32_t* p, uint32_t v) { asm volatile("st.release.gpu.global.u32 [%0], %1;" :: "l"(p), "r"(v) : "memory"); }
template<int ROLE = 0> __device__ __forceinline__ void wait_flag(const uint32_t* p, uint32_t target) {
  int n = 0; while (ld_acquire(p) < target) { __nanosleep(100); if (give_up(n, 5)) break; } }
__device__ __forceinline__ void fence_proxy_async() { asm volatile("fence.proxy.async;" ::: "memory"); }
__device__ __forceinline__ void mma16816(float* d, const uint32_t* a, uint32_t b0, uint32_t b1) {
  asm volatile("mma.sync.aligned.m16n8k16.row.col.f32.bf16.bf16.f32 {%0,%1,%2,%3}, {%4,%5,%6,%7}, {%8,%9}, {%0,%1,%2,%3};"
    : "+f"(d[0]), "+f"(d[1]), "+f"(d[2]), "+f"(d[3]) : "r"(a[0]), "r"(a[1]), "r"(a[2]), "r"(a[3]), "r"(b0), "r"(b1)); }
__device__ __forceinline__ void mma16816_4(float* d, uint32_t a0, uint32_t a1, uint32_t a2, uint32_t a3, uint32_t b0, uint32_t b1) {
  asm volatile("mma.sync.aligned.m16n8k16.row.col.f32.bf16.bf16.f32 {%0,%1,%2,%3}, {%4,%5,%6,%7}, {%8,%9}, {%0,%1,%2,%3};"
    : "+f"(d[0]), "+f"(d[1]), "+f"(d[2]), "+f"(d[3]) : "r"(a0), "r"(a1), "r"(a2), "r"(a3), "r"(b0), "r"(b1)); }
__device__ __forceinline__ void mma1688(float* d, uint32_t a0, uint32_t a1, uint32_t b0) {
  asm volatile("mma.sync.aligned.m16n8k8.row.col.f32.bf16.bf16.f32 {%0,%1,%2,%3}, {%4,%5}, {%6}, {%0,%1,%2,%3};"
    : "+f"(d[0]), "+f"(d[1]), "+f"(d[2]), "+f"(d[3]) : "r"(a0), "r"(a1), "r"(b0)); }
__device__ __forceinline__ void ldsm4(uint32_t* r, uint32_t addr) { asm volatile("ldmatrix.sync.aligned.m8n8.x4.shared.b16 {%0,%1,%2,%3}, [%4];" : "=r"(r[0]), "=r"(r[1]), "=r"(r[2]), "=r"(r[3]) : "r"(addr) : "memory"); }
__device__ __forceinline__ void ldsm4t(uint32_t* r, uint32_t addr) { asm volatile("ldmatrix.sync.aligned.m8n8.x4.trans.shared.b16 {%0,%1,%2,%3}, [%4];" : "=r"(r[0]), "=r"(r[1]), "=r"(r[2]), "=r"(r[3]) : "r"(addr) : "memory"); }
__device__ __forceinline__ void stsm4(uint32_t addr, uint32_t a, uint32_t b, uint32_t c, uint32_t d) { asm volatile("stmatrix.sync.aligned.m8n8.x4.shared.b16 [%0], {%1,%2,%3,%4};" :: "r"(addr), "r"(a), "r"(b), "r"(c), "r"(d) : "memory"); }
__device__ __forceinline__ uint32_t movm(uint32_t a) { uint32_t d; asm volatile("movmatrix.sync.aligned.m8n8.trans.b16 %0, %1;" : "=r"(d) : "r"(a)); return d; }
__device__ __forceinline__ uint32_t pack_bf16(float lo, float hi) { uint32_t d; asm("cvt.rn.bf16x2.f32 %0, %1, %2;" : "=r"(d) : "f"(hi), "f"(lo)); return d; }
__device__ __forceinline__ float bf16r(float x) { return __uint_as_float(pack_bf16(0.f, x)); }
__device__ __forceinline__ float bflo(uint32_t v) { return __uint_as_float(v << 16); }
__device__ __forceinline__ float bfhi(uint32_t v) { return __uint_as_float(v & 0xffff0000u); }
__device__ __forceinline__ uint32_t clk32() { uint32_t c; asm volatile("mov.u32 %0, %%clock;" : "=r"(c)); return c; }
__device__ __forceinline__ void lds128(uint32_t* r, uint32_t a) { asm volatile("ld.shared.v4.b32 {%0,%1,%2,%3}, [%4];" : "=r"(r[0]), "=r"(r[1]), "=r"(r[2]), "=r"(r[3]) : "r"(a) : "memory"); }
__device__ __forceinline__ void lds64(uint32_t* r, uint32_t a) { asm volatile("ld.shared.v2.b32 {%0,%1}, [%2];" : "=r"(r[0]), "=r"(r[1]) : "r"(a) : "memory"); }
__device__ __forceinline__ uint32_t lds32(uint32_t a) { uint32_t r; asm volatile("ld.shared.b32 %0, [%1];" : "=r"(r) : "r"(a) : "memory"); return r; }
__device__ __forceinline__ uint32_t lds16(uint32_t a) { uint16_t r; asm volatile("ld.shared.u16 %0, [%1];" : "=h"(r) : "r"(a) : "memory"); return r; }
__device__ __forceinline__ void sts128(uint32_t a, uint32_t x, uint32_t y, uint32_t z, uint32_t w) { asm volatile("st.shared.v4.b32 [%0], {%1,%2,%3,%4};" :: "r"(a), "r"(x), "r"(y), "r"(z), "r"(w) : "memory"); }
__device__ __forceinline__ void sts64(uint32_t a, uint32_t x, uint32_t y) { asm volatile("st.shared.v2.b32 [%0], {%1,%2};" :: "r"(a), "r"(x), "r"(y) : "memory"); }
__device__ __forceinline__ void sts32(uint32_t a, uint32_t x) { asm volatile("st.shared.b32 [%0], %1;" :: "r"(a), "r"(x) : "memory"); }
__device__ __forceinline__ void sts16(uint32_t a, uint32_t x) { asm volatile("st.shared.u16 [%0], %1;" :: "r"(a), "h"((uint16_t)x) : "memory"); }
__device__ __forceinline__ float ex2(float x) { float y; asm("ex2.approx.ftz.f32 %0, %1;" : "=f"(y) : "f"(x)); return y; }
__device__ __forceinline__ float rcp(float x) { float y; asm("rcp.approx.ftz.f32 %0, %1;" : "=f"(y) : "f"(x)); return y; }
__device__ __forceinline__ void tma_load(uint32_t dst, const CUtensorMap* tm, int c0, int c1, uint32_t bar) {
  asm volatile("cp.async.bulk.tensor.2d.shared::cluster.global.mbarrier::complete_tx::bytes [%0], [%1, {%3, %4}], [%2];"
    :: "r"(dst), "l"((uint64_t)tm), "r"(bar), "r"(c0), "r"(c1) : "memory"); }
__device__ __forceinline__ void tma_store(const CUtensorMap* tm, uint32_t src, int c0, int c1) {
  asm volatile("cp.async.bulk.tensor.2d.global.shared::cta.bulk_group [%0, {%2, %3}], [%1];" :: "l"((uint64_t)tm), "r"(src), "r"(c0), "r"(c1) : "memory"); }
__device__ __forceinline__ void tma_commit() { asm volatile("cp.async.bulk.commit_group;" ::: "memory"); }
__device__ __forceinline__ void tma_wait_read0() { asm volatile("cp.async.bulk.wait_group.read 0;" ::: "memory"); }
__device__ __forceinline__ void tma_wait0() { asm volatile("cp.async.bulk.wait_group 0;" ::: "memory"); }
__device__ __forceinline__ void wg_fence() { asm volatile("wgmma.fence.sync.aligned;" ::: "memory"); }
__device__ __forceinline__ void wg_commit() { asm volatile("wgmma.commit_group.sync.aligned;" ::: "memory"); }
template<int N> __device__ __forceinline__ void wg_wait() { asm volatile("wgmma.wait_group.sync.aligned %0;" :: "n"(N) : "memory"); }
__device__ __forceinline__ uint64_t make_desc(uint32_t addr, uint32_t lbo, uint32_t sbo) {
  return (uint64_t)((addr & 0x3FFFF) >> 4) | ((uint64_t)(lbo >> 4) << 16) | ((uint64_t)(sbo >> 4) << 32) | (1ull << 62); }
__device__ __forceinline__ void wgmma_n128(float* d, uint64_t da, uint64_t db, int scale_d) {
  asm volatile("{ .reg .pred p; setp.ne.b32 p, %66, 0;\n"
    "wgmma.mma_async.sync.aligned.m64n128k16.f32.bf16.bf16 {%0, %1, %2, %3, %4, %5, %6, %7, %8, %9, %10, %11, %12, %13, %14, %15, %16, %17, %18, %19, %20, %21, %22, %23, %24, %25, %26, %27, %28, %29, %30, %31, %32, %33, %34, %35, %36, %37, %38, %39, %40, %41, %42, %43, %44, %45, %46, %47, %48, %49, %50, %51, %52, %53, %54, %55, %56, %57, %58, %59, %60, %61, %62, %63}, %64, %65, p, 1, 1, 0, 1; }"
    : "+f"(d[0]), "+f"(d[1]), "+f"(d[2]), "+f"(d[3]), "+f"(d[4]), "+f"(d[5]), "+f"(d[6]), "+f"(d[7]), "+f"(d[8]), "+f"(d[9]), "+f"(d[10]), "+f"(d[11]), "+f"(d[12]), "+f"(d[13]), "+f"(d[14]), "+f"(d[15]), "+f"(d[16]), "+f"(d[17]), "+f"(d[18]), "+f"(d[19]), "+f"(d[20]), "+f"(d[21]), "+f"(d[22]), "+f"(d[23]), "+f"(d[24]), "+f"(d[25]), "+f"(d[26]), "+f"(d[27]), "+f"(d[28]), "+f"(d[29]), "+f"(d[30]), "+f"(d[31]), "+f"(d[32]), "+f"(d[33]), "+f"(d[34]), "+f"(d[35]), "+f"(d[36]), "+f"(d[37]), "+f"(d[38]), "+f"(d[39]), "+f"(d[40]), "+f"(d[41]), "+f"(d[42]), "+f"(d[43]), "+f"(d[44]), "+f"(d[45]), "+f"(d[46]), "+f"(d[47]), "+f"(d[48]), "+f"(d[49]), "+f"(d[50]), "+f"(d[51]), "+f"(d[52]), "+f"(d[53]), "+f"(d[54]), "+f"(d[55]), "+f"(d[56]), "+f"(d[57]), "+f"(d[58]), "+f"(d[59]), "+f"(d[60]), "+f"(d[61]), "+f"(d[62]), "+f"(d[63])
    : "l"(da), "l"(db), "r"(scale_d));
}

__device__ __forceinline__ void wgmma_n256(float* d, uint64_t da, uint64_t db, int scale_d) {
  asm volatile("{ .reg .pred p; setp.ne.b32 p, %130, 0;\n"
    "wgmma.mma_async.sync.aligned.m64n256k16.f32.bf16.bf16 {%0, %1, %2, %3, %4, %5, %6, %7, %8, %9, %10, %11, %12, %13, %14, %15, %16, %17, %18, %19, %20, %21, %22, %23, %24, %25, %26, %27, %28, %29, %30, %31, %32, %33, %34, %35, %36, %37, %38, %39, %40, %41, %42, %43, %44, %45, %46, %47, %48, %49, %50, %51, %52, %53, %54, %55, %56, %57, %58, %59, %60, %61, %62, %63, %64, %65, %66, %67, %68, %69, %70, %71, %72, %73, %74, %75, %76, %77, %78, %79, %80, %81, %82, %83, %84, %85, %86, %87, %88, %89, %90, %91, %92, %93, %94, %95, %96, %97, %98, %99, %100, %101, %102, %103, %104, %105, %106, %107, %108, %109, %110, %111, %112, %113, %114, %115, %116, %117, %118, %119, %120, %121, %122, %123, %124, %125, %126, %127}, %128, %129, p, 1, 1, 0, 1; }"
    : "+f"(d[0]), "+f"(d[1]), "+f"(d[2]), "+f"(d[3]), "+f"(d[4]), "+f"(d[5]), "+f"(d[6]), "+f"(d[7]), "+f"(d[8]), "+f"(d[9]), "+f"(d[10]), "+f"(d[11]), "+f"(d[12]), "+f"(d[13]), "+f"(d[14]), "+f"(d[15]), "+f"(d[16]), "+f"(d[17]), "+f"(d[18]), "+f"(d[19]), "+f"(d[20]), "+f"(d[21]), "+f"(d[22]), "+f"(d[23]), "+f"(d[24]), "+f"(d[25]), "+f"(d[26]), "+f"(d[27]), "+f"(d[28]), "+f"(d[29]), "+f"(d[30]), "+f"(d[31]), "+f"(d[32]), "+f"(d[33]), "+f"(d[34]), "+f"(d[35]), "+f"(d[36]), "+f"(d[37]), "+f"(d[38]), "+f"(d[39]), "+f"(d[40]), "+f"(d[41]), "+f"(d[42]), "+f"(d[43]), "+f"(d[44]), "+f"(d[45]), "+f"(d[46]), "+f"(d[47]), "+f"(d[48]), "+f"(d[49]), "+f"(d[50]), "+f"(d[51]), "+f"(d[52]), "+f"(d[53]), "+f"(d[54]), "+f"(d[55]), "+f"(d[56]), "+f"(d[57]), "+f"(d[58]), "+f"(d[59]), "+f"(d[60]), "+f"(d[61]), "+f"(d[62]), "+f"(d[63]), "+f"(d[64]), "+f"(d[65]), "+f"(d[66]), "+f"(d[67]), "+f"(d[68]), "+f"(d[69]), "+f"(d[70]), "+f"(d[71]), "+f"(d[72]), "+f"(d[73]), "+f"(d[74]), "+f"(d[75]), "+f"(d[76]), "+f"(d[77]), "+f"(d[78]), "+f"(d[79]), "+f"(d[80]), "+f"(d[81]), "+f"(d[82]), "+f"(d[83]), "+f"(d[84]), "+f"(d[85]), "+f"(d[86]), "+f"(d[87]), "+f"(d[88]), "+f"(d[89]), "+f"(d[90]), "+f"(d[91]), "+f"(d[92]), "+f"(d[93]), "+f"(d[94]), "+f"(d[95]), "+f"(d[96]), "+f"(d[97]), "+f"(d[98]), "+f"(d[99]), "+f"(d[100]), "+f"(d[101]), "+f"(d[102]), "+f"(d[103]), "+f"(d[104]), "+f"(d[105]), "+f"(d[106]), "+f"(d[107]), "+f"(d[108]), "+f"(d[109]), "+f"(d[110]), "+f"(d[111]), "+f"(d[112]), "+f"(d[113]), "+f"(d[114]), "+f"(d[115]), "+f"(d[116]), "+f"(d[117]), "+f"(d[118]), "+f"(d[119]), "+f"(d[120]), "+f"(d[121]), "+f"(d[122]), "+f"(d[123]), "+f"(d[124]), "+f"(d[125]), "+f"(d[126]), "+f"(d[127])
    : "l"(da), "l"(db), "r"(scale_d));
}

__device__ __align__(1024) bf16 g_KV[2 * SEQ][HD];
__device__ __align__(1024) bf16 g_KVm[2 * NSEG * NM][HD];
__device__ __align__(1024) bf16 g_O[SEQ][HD];
__device__ __align__(1024) float g_P[4][SEQ][DM];
__device__ __align__(1024) bf16 g_B[SEQ][DM];
__device__ float g_gate[SEQ];
__device__ __align__(128) uint32_t g_part[2][64][32][80];
__device__ __align__(128) uint32_t g_mem[2][5120];
struct Flags {
  uint32_t task_ctr, exit_ctr, pad0[30];
  uint32_t kv[16][32];
  uint32_t prog[64][8];
  uint32_t o_rdy[16][4];
  uint32_t op_cnt[16][8];
  uint32_t conv[8];
  uint32_t gate[16];
};
__device__ __align__(128) Flags g_f;

struct Params {
  CUtensorMap tmX, tmO, tmKV, tmKVm, tmWq, tmWk, tmWv, tmWo;
  const bf16 *x, *mem0, *Wq, *Wk, *Wv, *Wo, *bk, *bv, *shift_k, *ssm_k, *ssm_D, *gate_w;
  bf16* out;
  int dG, dG2;
  int t_begin, t_end, do_chain, do_reset;
};

constexpr int N_KV = 512, N_GATE = 16, N_CONV = 80, N_RB = 32 + 20;
constexpr int T_GATE = N_KV, T_CONV = T_GATE + N_GATE, T_RB = T_CONV + N_CONV, N_TASKS = T_RB + 16 * N_RB;

constexpr int STAGE = 49152, NST = 4;
constexpr int B_STG = NST * STAGE;
constexpr int B_BAR = B_STG + 32768;
constexpr int SMEM_TOTAL = B_BAR + 1024;
constexpr int BR_FULL = 0, BR_EMPTY = 32, BR_TQF = 64, BR_TQE = 80, BR_TASK = 96, BR_X = 128, BR_KVF = 136, BR_KVE = 152, BR_PUB = 168, BR_MISC = 192;

#define KR 12
constexpr int WR = 8;
constexpr int NSQ = (20 - KR) * 3;
constexpr int NSF_LO = NSQ + 16, NSF_HI = NSQ + 8;
constexpr int OFF_WF = 0;
constexpr int OFF_RT = OFF_WF + 4 * (NSF_LO + NSF_HI) * 512;
constexpr int OFF_MEMB = OFF_RT;
constexpr int OFF_RED = OFF_MEMB + 10240;
constexpr int OFF_SP = OFF_RED + 6144;
constexpr int OFF_SX = OFF_SP + 5120;
constexpr int OFF_VM = OFF_SX + 2560;
constexpr int OFF_O = OFF_VM + 2048;
constexpr int OFF_KX = OFF_O + 2048;
constexpr int OFF_VX = OFF_KX + 9216;
constexpr int OFF_RT_END = OFF_VX + 17408;
static_assert(OFF_RT + 480 * 144 <= B_BAR && OFF_RT_END <= B_BAR, "chain smem");
#define STAMP(i)

__device__ __forceinline__ void chain_prefetch(const uint32_t sbase, int s, int h, int j, int lane) {
  const int b = s & 1;
  if ((s & 3) == 0) {
    if (lane == 0) { wait_flag<1>(&g_f.kv[s >> 2][h >> 1], 2); wait_flag<1>(&g_f.kv[s >> 2][16 + (h >> 1)], 2); }
    __syncwarp();
  }
  const bf16* kp = &g_KV[s * SEG][h * DH + j * 64];
  const bf16* vp = &g_KV[SEQ + s * SEG][h * DH];
#pragma unroll 2
  for (int k = 0; k < 8; k++) { int c = lane + 32 * k;
    asm volatile("cp.async.cg.shared.global [%0], [%1], 16;" :: "r"(sbase + OFF_KX + b * 4608 + (c >> 3) * 144 + (c & 7) * 16), "l"(kp + (size_t)(c >> 3) * HD + (c & 7) * 8) : "memory"); }
#pragma unroll 2
  for (int k = 0; k < 16; k++) { int c = lane + 32 * k;
    asm volatile("cp.async.cg.shared.global [%0], [%1], 16;" :: "r"(sbase + OFF_VX + b * 8704 + (c >> 4) * 272 + (c & 15) * 16), "l"(vp + (size_t)(c >> 4) * HD + (c & 15) * 8) : "memory"); }
  asm volatile("cp.async.mbarrier.arrive.noinc.shared::cta.b64 [%0];" :: "r"(sbase + B_BAR + BR_KVF + 8 * b) : "memory");
}

__device__ __forceinline__ void chain_producer(const uint32_t sbase) {
  const int lane = threadIdx.x & 31;
  const int h = blockIdx.x >> 1, j = blockIdx.x & 1;
  bar_sync(2, 288);
  chain_prefetch(sbase, 0, h, j, lane);
  chain_prefetch(sbase, 1, h, j, lane);
  for (int s = 0; s < NSEG; s++) {
    mbar_wait<1>(sbase + B_BAR + BR_PUB, s & 1);
    if (lane == 0) { __threadfence(); st_release(&g_f.prog[blockIdx.x][0], s + 1); }
    if (s + 2 < NSEG) {
      mbar_wait<1>(sbase + B_BAR + BR_KVE + 8 * (s & 1), (s >> 1) & 1);
      chain_prefetch(sbase, s + 2, h, j, lane);
    }
  }
}

__device__ __forceinline__ void chain_consumer(const Params& a, unsigned char* sm, const uint32_t sbase) {
    const int tid = opaque_tid(), lane = tid & 31, warp = tid >> 5;
    const int h = blockIdx.x >> 1, j = blockIdx.x & 1;
    const uint32_t bar_x = sbase + B_BAR + BR_X, bar_full = sbase + B_BAR + BR_KVF, bar_empty = sbase + B_BAR + BR_KVE, bar_pub = sbase + B_BAR + BR_PUB;
    const int kg = warp >> 2, mg = warp & 3;
    uint32_t wA[KR * 3][4];
    uint32_t wO[WR][4];
    const uint32_t swf0 = sbase + OFF_WF + (warp < 4 ? warp * NSF_LO : 4 * NSF_LO + (warp - 4) * NSF_HI) * 512 + lane * 16;
    {
      unsigned char* stg = sm + OFF_RT;
      const int li = lane >> 3, lr = lane & 7;
#pragma unroll
      for (int ch = 0; ch < 4; ch++) {
        uint4 v[15];
#pragma unroll
        for (int k = 0; k < 15; k++) {
          int idx = tid + 256 * k; int row = idx >> 3, cc = idx & 7;
          int mk = row / 80, r = row - mk * 80; int mat = mk >> 1, kgi = mk & 1;
          const bf16* W = mat == 0 ? a.Wq : (mat == 1 ? a.Wk : a.Wv);
          v[k] = __ldg((const uint4*)(W + (size_t)(320 * kgi + 80 * ch + r) * HD + h * DH + j * 64 + cc * 8));
        }
#pragma unroll
        for (int k = 0; k < 15; k++) { int idx = tid + 256 * k; *(uint4*)(stg + (idx >> 3) * 144 + (idx & 7) * 16) = v[k]; }
        bar_sync(1, 256);
#pragma unroll
        for (int kk = 0; kk < 5; kk++) {
          const int ks = ch * 5 + kk;
#pragma unroll
          for (int mat = 0; mat < 3; mat++) {
            uint32_t addr = smem_u32(stg) + ((mat * 2 + kg) * 80 + kk * 16 + (li >> 1) * 8 + lr) * 144 + (mg * 16 + (li & 1) * 8) * 2;
            if (ks < KR) ldsm4t(wA[ks * 3 + mat], addr);
            else { uint32_t t[4]; ldsm4t(t, addr); sts128(swf0 + ((ks - KR) * 3 + mat) * 512, t[0], t[1], t[2], t[3]); }
          }
        }
        bar_sync(1, 256);
      }
#pragma unroll
      for (int ch = 0; ch < 2; ch++) {
        uint4 v[10];
#pragma unroll
        for (int k = 0; k < 10; k++) {
          int idx = tid + 256 * k; int row = idx / 40, cc = idx - row * 40;
          v[k] = __ldg((const uint4*)(a.Wo + (size_t)(h * DH + ch * 64 + row) * DM + j * 320 + cc * 8));
        }
#pragma unroll
        for (int k = 0; k < 10; k++) { int idx = tid + 256 * k; int row = idx / 40, cc = idx - row * 40; *(uint4*)(stg + row * 656 + cc * 16) = v[k]; }
        bar_sync(1, 256);
#pragma unroll
        for (int i = 0; i < 3; i++) {
          if (i == 2 && warp >= 4) break;
          const int t = i < 2 ? warp + 8 * i : 16 + warp;
#pragma unroll
          for (int kk = 0; kk < 4; kk++) {
            const int f = i * 8 + ch * 4 + kk;
            uint32_t addr = smem_u32(stg) + (kk * 16 + (li >> 1) * 8 + lr) * 656 + (t * 16 + (li & 1) * 8) * 2;
            if (f < WR) ldsm4t(wO[f], addr);
            else { uint32_t tt[4]; ldsm4t(tt, addr); sts128(swf0 + (NSQ + f - WR) * 512, tt[0], tt[1], tt[2], tt[3]); }
          }
        }
        bar_sync(1, 256);
      }
    }
    bar_sync(2, 288);
    if (tid == 0) mbar_expect_tx(bar_x, 2 * 2304);
    const uint32_t peer_off = mapa(sbase, j ^ 1) - sbase;
    const uint32_t self_off = mapa(sbase, j) - sbase;
    const float scale = 0.08838834764831845f;
    const int rme = 32 * j + h;
    uint32_t Q[6][4];
#pragma unroll
    for (int k = 0; k < 5; k++) {
      int c = tid + 256 * k; int ks = c >> 5, l = c & 31; int gg = l >> 2, cc = l & 3;
      uint32_t b0 = *(const uint32_t*)(a.mem0 + gg * DM + ks * 16 + 2 * cc), b1 = *(const uint32_t*)(a.mem0 + gg * DM + ks * 16 + 8 + 2 * cc);
      sts64(sbase + OFF_MEMB + c * 8, b0, b1);
    }
#pragma unroll
    for (int n = 0; n < 6; n++) lds128(Q[n], swf0 + n * 512);
    for (int s = 0; s < NSEG; s++) {
      const int b = s & 1;
      const int tid = opaque_tid();
      const int lane = tid & 31, warp = tid >> 5;
      const int kg = warp >> 2, mg = warp & 3;
      const int g = lane >> 2, c4 = lane & 3;
      const uint32_t swf = sbase + OFF_WF + (warp < 4 ? warp * NSF_LO : 4 * NSF_LO + (warp - 4) * NSF_HI) * 512 + lane * 16;
      bar_sync(1, 256);
      STAMP(1);
      float acc[3][4];
#pragma unroll
      for (int m = 0; m < 3; m++) { acc[m][0] = acc[m][1] = acc[m][2] = acc[m][3] = 0.f; }
      {
        const uint32_t bb = sbase + OFF_MEMB + (kg * 20 * 32 + lane) * 8;
        constexpr int NS = 20 - KR;
        uint32_t br[2][2], bs[2][2];
        lds64(br[0], bb); lds64(bs[0], bb + KR * 256);
#pragma unroll
        for (int i = 0; i < KR; i++) {
          if (i + 1 < KR) lds64(br[(i + 1) & 1], bb + (i + 1) * 256);
          if (i + 1 < NS) lds64(bs[(i + 1) & 1], bb + (KR + i + 1) * 256);
#pragma unroll
          for (int m = 0; m < 3; m++) mma16816(acc[m], wA[i * 3 + m], br[i & 1][0], br[i & 1][1]);
          if (i < NS) {
#pragma unroll
            for (int m = 0; m < 3; m++) {
              const int n = i * 3 + m;
              mma16816(acc[m], Q[n % 6], bs[i & 1][0], bs[i & 1][1]);
              if (n + 6 < NSQ) lds128(Q[n % 6], swf + (n + 6) * 512);
            }
          }
        }
      }
      STAMP(2);
      const uint32_t red = sbase + OFF_RED + mg * 1536 + lane * 16;
      if (kg == 0) sts128(red + 1024, __float_as_uint(acc[2][0]), __float_as_uint(acc[2][1]), __float_as_uint(acc[2][2]), __float_as_uint(acc[2][3]));
      else { sts128(red, __float_as_uint(acc[0][0]), __float_as_uint(acc[0][1]), __float_as_uint(acc[0][2]), __float_as_uint(acc[0][3]));
             sts128(red + 512, __float_as_uint(acc[1][0]), __float_as_uint(acc[1][1]), __float_as_uint(acc[1][2]), __float_as_uint(acc[1][3])); }
      mbar_wait(bar_full + 8 * b, (s >> 1) & 1);
      if (kg == 0) {
        uint32_t ka = sbase + OFF_KX + b * 4608 + (((lane >> 4) & 1) * 8 + (lane & 7)) * 144 + (mg * 16 + ((lane >> 3) & 1) * 8) * 2;
        ldsm4(Q[0], ka); ldsm4(Q[1], ka + 16 * 144);
      }
      bar_sync(3 + mg, 64);
      if (kg == 0) {
        lds128(Q[2], red); lds128(Q[3], red + 512);
        uint32_t q0 = movm(pack_bf16(acc[0][0] + __uint_as_float(Q[2][0]), acc[0][1] + __uint_as_float(Q[2][1]))), q1 = movm(pack_bf16(acc[0][2] + __uint_as_float(Q[2][2]), acc[0][3] + __uint_as_float(Q[2][3])));
        uint32_t k0 = movm(pack_bf16(acc[1][0] + __uint_as_float(Q[3][0]), acc[1][1] + __uint_as_float(Q[3][1]))), k1 = movm(pack_bf16(acc[1][2] + __uint_as_float(Q[3][2]), acc[1][3] + __uint_as_float(Q[3][3])));
        float sp[5][4];
#pragma unroll
        for (int t = 0; t < 5; t++) sp[t][0] = sp[t][1] = sp[t][2] = sp[t][3] = 0.f;
        mma16816_4(sp[1], q0, 0, q1, 0, Q[0][0], Q[0][1]);
        mma16816_4(sp[2], q0, 0, q1, 0, Q[0][2], Q[0][3]);
        mma16816_4(sp[3], q0, 0, q1, 0, Q[1][0], Q[1][1]);
        mma16816_4(sp[4], q0, 0, q1, 0, Q[1][2], Q[1][3]);
        mma16816_4(sp[0], q0, 0, q1, 0, k0, k1);
        const uint32_t spb = sbase + OFF_SP + mg * 1280 + lane * 8;
#pragma unroll
        for (int t = 0; t < 5; t++) sts64(spb + t * 256, __float_as_uint(sp[t][0]), __float_as_uint(sp[t][1]));
        bf16* kd = &g_KVm[s * NM + g][h * DH + j * 64 + mg * 16 + 2 * c4];
        *(uint32_t*)kd = k0; *(uint32_t*)(kd + 8) = k1;
      } else {
        lds128(Q[2], red + 1024);
        uint32_t v0 = pack_bf16(acc[2][0] + __uint_as_float(Q[2][0]), acc[2][1] + __uint_as_float(Q[2][1])), v1 = pack_bf16(acc[2][2] + __uint_as_float(Q[2][2]), acc[2][3] + __uint_as_float(Q[2][3]));
        uint32_t dst = sbase + OFF_VM + ((j * 4 + mg) * 32 + lane) * 8;
        if (s < NSEG - 1) {
          st_async_v2(dst + peer_off, v0, v1, bar_x + peer_off);
          st_async_v2(dst + self_off, v0, v1, bar_x + self_off);
        }
        uint32_t t0 = movm(v0), t1 = movm(v1);
        bf16* vd = &g_KVm[NSEG * NM + s * NM + g][h * DH + j * 64 + mg * 16 + 2 * c4];
        *(uint32_t*)vd = t0; *(uint32_t*)(vd + 8) = t1;
      }
      __syncwarp();
      if (lane == 0) mbar_arrive(bar_pub);
      if (s == NSEG - 1) break;
      bar_sync(1, 256);
      if (tid < 160) {
        uint32_t x0[2], x1[2], x2[2], x3[2];
        const uint32_t spb = sbase + OFF_SP + tid * 8;
        lds64(x0, spb); lds64(x1, spb + 1280); lds64(x2, spb + 2560); lds64(x3, spb + 3840);
        float sx = (__uint_as_float(x0[0]) + __uint_as_float(x1[0])) + (__uint_as_float(x2[0]) + __uint_as_float(x3[0]));
        float sy = (__uint_as_float(x0[1]) + __uint_as_float(x1[1])) + (__uint_as_float(x2[1]) + __uint_as_float(x3[1]));
        uint32_t dst = sbase + OFF_SX + (j * 160 + tid) * 8;
        st_async_v2(dst + peer_off, __float_as_uint(sx), __float_as_uint(sy), bar_x + peer_off);
        st_async_v2(dst + self_off, __float_as_uint(sx), __float_as_uint(sy), bar_x + self_off);
      }
      STAMP(3);
      uint32_t vx0[4], vx1[4];
      {
        uint32_t va = sbase + OFF_VX + b * 8704 + (((lane >> 3) & 1) * 8 + (lane & 7)) * 272 + (warp * 16 + (lane >> 4) * 8) * 2;
        ldsm4t(vx0, va); ldsm4t(vx1, va + 16 * 272);
      }
#pragma unroll
      for (int n = 0; n < 4; n++) lds128(Q[n], swf + (NSQ + n) * 512);
      mbar_wait(bar_x, s & 1);
      STAMP(4);
      float p[10];
      {
        const uint32_t sx = sbase + OFF_SX + lane * 8;
#pragma unroll
        for (int t = 0; t < 5; t++) { uint32_t u[2], w[2]; lds64(u, sx + t * 256); lds64(w, sx + 1280 + t * 256);
          uint32_t pk = pack_bf16(__uint_as_float(u[0]) + __uint_as_float(w[0]), __uint_as_float(u[1]) + __uint_as_float(w[1]));
          pk = pack_bf16(bflo(pk) * scale, bfhi(pk) * scale);
          p[2 * t] = bflo(pk); p[2 * t + 1] = bfhi(pk); }
      }
      uint32_t vm[2]; lds64(vm, sbase + OFF_VM + (warp * 32 + lane) * 8);
      float mx = fmaxf(fmaxf(fmaxf(p[0], p[1]), fmaxf(p[2], p[3])), fmaxf(fmaxf(fmaxf(p[4], p[5]), fmaxf(p[6], p[7])), fmaxf(p[8], p[9])));
      mx = fmaxf(mx, __shfl_xor_sync(0xffffffffu, mx, 1)); mx = fmaxf(mx, __shfl_xor_sync(0xffffffffu, mx, 2));
      const float mxl = mx * 1.4426950408889634f;
#pragma unroll
      for (int i = 0; i < 10; i++) p[i] = ex2(fmaf(p[i], 1.4426950408889634f, -mxl));
      float sum = (((p[0] + p[1]) + (p[2] + p[3])) + ((p[4] + p[5]) + (p[6] + p[7]))) + (p[8] + p[9]);
      sum += __shfl_xor_sync(0xffffffffu, sum, 1); sum += __shfl_xor_sync(0xffffffffu, sum, 2);
      const float inv = rcp(sum);
      uint32_t pa[5];
#pragma unroll
      for (int t = 0; t < 5; t++) pa[t] = pack_bf16(p[2 * t] * inv, p[2 * t + 1] * inv);
      {
        float o0[4] = {0.f, 0.f, 0.f, 0.f}, o1[4] = {0.f, 0.f, 0.f, 0.f}, o2[4] = {0.f, 0.f, 0.f, 0.f}, o3[4] = {0.f, 0.f, 0.f, 0.f}, o4[4] = {0.f, 0.f, 0.f, 0.f}, o5[4] = {0.f, 0.f, 0.f, 0.f};
        mma16816_4(o0, pa[1], 0, pa[2], 0, vx0[0], vx0[1]);
        mma16816_4(o1, pa[1], 0, pa[2], 0, vx0[2], vx0[3]);
        mma16816_4(o2, pa[3], 0, pa[4], 0, vx1[0], vx1[1]);
        mma16816_4(o3, pa[3], 0, pa[4], 0, vx1[2], vx1[3]);
        mma1688(o4, pa[0], 0, vm[0]);
        mma1688(o5, pa[0], 0, vm[1]);
        sts64(sbase + OFF_O + ((warp >> 1) * 32 + lane) * 16 + (warp & 1) * 8, pack_bf16(o0[0] + o2[0] + o4[0], o0[1] + o2[1] + o4[1]), pack_bf16(o1[0] + o3[0] + o5[0], o1[1] + o3[1] + o5[1]));
      }
      lds128(Q[4], swf + (NSQ + 4) * 512); lds128(Q[5], swf + (NSQ + 5) * 512);
      __syncwarp();
      if (lane == 0) mbar_arrive(bar_empty + 8 * b);
      bar_sync(1, 256);
      if (tid == 0 && s < NSEG - 2) mbar_expect_tx(bar_x, 2 * 2304);
      STAMP(5);
      const uint32_t t_5 = clk32();
      {
        uint32_t ob[4][4];
#pragma unroll
        for (int kp = 0; kp < 4; kp++) lds128(ob[kp], sbase + OFF_O + (kp * 32 + lane) * 16);
        const uint32_t tag = ((s >> 1) + 1) & 3;
#pragma unroll
        for (int i = 0; i < 3; i++) {
          if (i == 2 && warp >= 4) break;
          float d0[4] = {0.f, 0.f, 0.f, 0.f}, d1[4] = {0.f, 0.f, 0.f, 0.f};
#pragma unroll
          for (int ks = 0; ks < 8; ks++) {
            uint32_t b0 = ob[ks >> 1][(ks & 1) * 2], b1 = ob[ks >> 1][(ks & 1) * 2 + 1];
            float* d = (ks & 1) ? d1 : d0;
            if (i == 0) mma16816(d, wO[ks], b0, b1);
            else {
              const int n = (i - 1) * 8 + ks;
              mma16816(d, Q[n % 6], b0, b1);
              if (n + 6 < 8 || (n + 6 < 16 && warp < 4)) lds128(Q[n % 6], swf + (NSQ + n + 6) * 512);
            }
          }
          const int t = i < 2 ? warp + 8 * i : 16 + warp;
          const int U = (20 * j + t) * 16 + c4 * 4 + (g >> 1);
          const int r = U / 10;
          uint32_t* dst = &g_part[b][r][h][((U - r * 10) * 2 + (g & 1)) * 4];
          st_relaxed_v4(dst, (__float_as_uint(d0[0] + d1[0]) & ~3u) | tag, (__float_as_uint(d0[1] + d1[1]) & ~3u) | tag,
                             (__float_as_uint(d0[2] + d1[2]) & ~3u) | tag, (__float_as_uint(d0[3] + d1[3]) & ~3u) | tag);
        }
        STAMP(6);
        if (warp >= 3) {
          const int ch = 4 * (warp - 3) + (lane & 3);
          const uint32_t* src = &g_part[b][rme][lane >> 2][ch * 4];
          while ((int)(clk32() - t_5) < a.dG) {}
          uint4 v[4]; int spins = 0;
          while (true) {
#pragma unroll
            for (int k = 0; k < 4; k++) v[k] = ld_relaxed_v4(src + k * 8 * 80);
            uint32_t bad = 0;
#pragma unroll
            for (int k = 0; k < 4; k++) bad |= (v[k].x ^ tag) | (v[k].y ^ tag) | (v[k].z ^ tag) | (v[k].w ^ tag);
            if (__all_sync(0xffffffffu, !(bad & 3))) break;
            if (__any_sync(0xffffffffu, give_up(spins, 4))) break;
          }
          float x = (__uint_as_float(v[0].x) + __uint_as_float(v[1].x)) + (__uint_as_float(v[2].x) + __uint_as_float(v[3].x));
          float y = (__uint_as_float(v[0].y) + __uint_as_float(v[1].y)) + (__uint_as_float(v[2].y) + __uint_as_float(v[3].y));
          float z = (__uint_as_float(v[0].z) + __uint_as_float(v[1].z)) + (__uint_as_float(v[2].z) + __uint_as_float(v[3].z));
          float w = (__uint_as_float(v[0].w) + __uint_as_float(v[1].w)) + (__uint_as_float(v[2].w) + __uint_as_float(v[3].w));
          const bool h4 = lane & 16, h3 = lane & 8;
          float e0 = (h4 ? z : x) + __shfl_xor_sync(0xffffffffu, h4 ? x : z, 16);
          float e1 = (h4 ? w : y) + __shfl_xor_sync(0xffffffffu, h4 ? y : w, 16);
          float f = (h3 ? e1 : e0) + __shfl_xor_sync(0xffffffffu, h3 ? e0 : e1, 8);
          f += __shfl_xor_sync(0xffffffffu, f, 4);
          if (!(lane & 4)) {
            const int widx = (rme * 10 + (ch >> 1)) * 8 + (h3 ? 4 : 0) + (h4 ? 2 : 0) + (ch & 1);
            uint32_t word = (pack_bf16(0.f, f)) | (uint32_t)(s + 1);
            st_relaxed(&g_mem[b ^ 1][widx], word);
          }
        }
      }
      STAMP(7);
      {
#pragma unroll
        for (int n = 0; n < 3; n++) lds128(Q[n], swf + n * 512);
        const uint32_t* src = &g_mem[b ^ 1][tid * 4];
        while ((int)(clk32() - t_5) < a.dG2) {}
        uint4 v[5]; int spins = 0;
        const uint32_t sq = s + 1;
        while (true) {
#pragma unroll
          for (int k = 0; k < 5; k++) v[k] = ld_relaxed_v4(src + 1024 * k);
          uint32_t bad = 0;
#pragma unroll
          for (int k = 0; k < 5; k++) bad |= (v[k].x ^ sq) | (v[k].y ^ sq) | (v[k].z ^ sq) | (v[k].w ^ sq);
          if (!(bad & 0xffff)) break;
          if (give_up(spins, 3)) break;
        }
        const int u = (lane >> 1);
        const uint32_t dst = sbase + OFF_MEMB + (warp * 32 + (2 * (u >> 2) + (lane & 1)) * 4 + (u & 3)) * 8;
#pragma unroll
        for (int k = 0; k < 5; k++) sts64(dst + k * 2048, __byte_perm(v[k].x, v[k].y, 0x7632), __byte_perm(v[k].z, v[k].w, 0x7632));
#pragma unroll
        for (int n = 3; n < 6; n++) lds128(Q[n], swf + n * 512);
      }
      STAMP(0);
    }
}

struct Ring { uint32_t st, ph; __device__ __forceinline__ void next() { if (++st == NST) { st = 0; ph ^= 1; } } };

__device__ __forceinline__ void bulk_producer(const Params& p, const uint32_t sbase) {
  Ring r{0, 1};
  const uint32_t bb = sbase + B_BAR;
  for (int it = 0;; it++) {
    const int slot = it & 1;
    mbar_wait<1>(bb + BR_TQE + 8 * slot, ((it >> 1) & 1) ^ 1);
    int t = p.t_begin + (int)atomicAdd(&g_f.task_ctr, 1u);
    if (t >= p.t_end) t = N_TASKS;
    sts32(bb + BR_TASK + 4 * slot, t);
    mbar_arrive(bb + BR_TQF + 8 * slot);
    if (t >= N_TASKS) break;
    if (t < N_KV) {
      const int rb = t >> 5, ct = t & 31;
      const CUtensorMap* tw = ct < 16 ? &p.tmWk : &p.tmWv;
      const int n0 = (ct & 15) * 256;
      for (int kb = 0; kb < 10; kb++) {
        mbar_wait<1>(bb + BR_EMPTY + 8 * r.st, r.ph);
        const uint32_t fb = bb + BR_FULL + 8 * r.st, sa = sbase + r.st * STAGE;
        mbar_expect_tx(fb, 49152);
        tma_load(sa, &p.tmX, kb * 64, rb * 128, fb);
        tma_load(sa + 8192, &p.tmX, kb * 64, rb * 128 + 64, fb);
#pragma unroll
        for (int q = 0; q < 4; q++) tma_load(sa + 16384 + q * 8192, tw, n0 + q * 64, kb * 64, fb);
        r.next();
      }
    } else if (t < T_RB) {
      mbar_wait<1>(bb + BR_TQE + 8 * slot, (it >> 1) & 1);
    } else {
      const int rb = (t - T_RB) / N_RB, q = (t - T_RB) - rb * N_RB;
      if (q < 32) {
        const int h = q;
        for (int kb = 0; kb < 10; kb++) {
          mbar_wait<1>(bb + BR_EMPTY + 8 * r.st, r.ph);
          const uint32_t fb = bb + BR_FULL + 8 * r.st, sa = sbase + r.st * STAGE;
          mbar_expect_tx(fb, 32768);
          tma_load(sa, &p.tmX, kb * 64, rb * 128, fb);
          tma_load(sa + 8192, &p.tmX, kb * 64, rb * 128 + 64, fb);
          tma_load(sa + 16384, &p.tmWq, h * 128, kb * 64, fb);
          tma_load(sa + 24576, &p.tmWq, h * 128 + 64, kb * 64, fb);
          r.next();
        }
        wait_flag<1>(&g_f.kv[rb][h >> 1], 2); wait_flag<1>(&g_f.kv[rb][16 + (h >> 1)], 2);
        wait_flag<1>(&g_f.prog[2 * h][0], 4 * rb + 4); wait_flag<1>(&g_f.prog[2 * h + 1][0], 4 * rb + 4);
        fence_proxy_async();
        for (int kv = 0; kv < 2; kv++) {
          mbar_wait<1>(bb + BR_EMPTY + 8 * r.st, r.ph);
          const uint32_t fb = bb + BR_FULL + 8 * r.st, sa = sbase + r.st * STAGE;
          mbar_expect_tx(fb, 40960);
#pragma unroll
          for (int eh = 0; eh < 2; eh++) {
            tma_load(sa + eh * 16384, &p.tmKV, h * 128 + eh * 64, kv * SEQ + rb * 128, fb);
            tma_load(sa + eh * 16384 + 8192, &p.tmKV, h * 128 + eh * 64, kv * SEQ + rb * 128 + 64, fb);
            tma_load(sa + 32768 + eh * 4096, &p.tmKVm, h * 128 + eh * 64, kv * 512 + rb * 32, fb);
          }
          r.next();
        }
      } else {
        const int ct = (q - 32) >> 2, kc = (q - 32) & 3;
        wait_flag<1>(&g_f.o_rdy[rb][kc], 16);
        fence_proxy_async();
        for (int kb = 0; kb < 16; kb++) {
          mbar_wait<1>(bb + BR_EMPTY + 8 * r.st, r.ph);
          const uint32_t fb = bb + BR_FULL + 8 * r.st, sa = sbase + r.st * STAGE;
          mbar_expect_tx(fb, 32768);
          const int k0 = kc * 1024 + kb * 64;
          tma_load(sa, &p.tmO, k0, rb * 128, fb);
          tma_load(sa + 8192, &p.tmO, k0, rb * 128 + 64, fb);
          tma_load(sa + 16384, &p.tmWo, ct * 128, k0, fb);
          tma_load(sa + 24576, &p.tmWo, ct * 128 + 64, k0, fb);
          r.next();
        }
      }
    }
  }
}

template<int N>
__device__ __forceinline__ void gemm_mainloop(float* acc, Ring& r, const uint32_t sbase, int nkb, int wg, bool elect) {
  const uint32_t bb = sbase + B_BAR;
  uint32_t prev = 0;
#pragma unroll
  for (int i = 0; i < N / 2; i++) acc[i] = 0.f;
  for (int kb = 0; kb < nkb; kb++) {
    mbar_wait(bb + BR_FULL + 8 * r.st, r.ph);
    const uint32_t sa = sbase + r.st * STAGE;
    const uint64_t da = make_desc(sa + wg * 8192, 16, 1024);
    const uint64_t db = make_desc(sa + 16384, 8192, 1024);
    wg_fence();
#pragma unroll
    for (int k = 0; k < 4; k++) {
      if (N == 256) wgmma_n256(acc, da + k * 2, db + k * 128, (kb | k) != 0);
      else wgmma_n128(acc, da + k * 2, db + k * 128, (kb | k) != 0);
    }
    wg_commit();
    if (kb > 0) { wg_wait<1>(); if (elect) mbar_arrive(bb + BR_EMPTY + 8 * prev); }
    prev = r.st;
    r.next();
  }
  wg_wait<0>();
  if (elect) mbar_arrive(bb + BR_EMPTY + 8 * prev);
}

__device__ __forceinline__ void store_tile128(const float* acc, const uint32_t stg, const CUtensorMap* tm, int col0, int row0, int wq, int lane, int wg, bool elect) {
  const int i = lane >> 3, rr = lane & 7;
  const int row = wq * 16 + (i & 1) * 8 + rr;
#pragma unroll
  for (int jj = 0; jj < 16; jj += 2) {
    const int chunk = jj + (i >> 1);
    const uint32_t addr = stg + (chunk >> 3) * 8192 + row * 128 + (((chunk & 7) ^ rr) << 4);
    stsm4(addr, pack_bf16(acc[jj * 4 + 0], acc[jj * 4 + 1]), pack_bf16(acc[jj * 4 + 2], acc[jj * 4 + 3]),
                pack_bf16(acc[jj * 4 + 4], acc[jj * 4 + 5]), pack_bf16(acc[jj * 4 + 6], acc[jj * 4 + 7]));
  }
  fence_proxy_async();
  bar_sync(7 + wg, 128);
  if (elect) { tma_store(tm, stg, col0, row0); tma_store(tm, stg + 8192, col0 + 64, row0); tma_commit(); }
}

__device__ __forceinline__ void task_kv(const Params& p, Ring& r, const uint32_t sbase, int t) {
  const int tid = opaque_tid(), lane = tid & 31, wg = tid >> 7, wq = (tid >> 5) & 3;
  const bool elect = (tid & 127) == 0;
  const int rb = t >> 5, ct = t & 31;
  float acc[128];
  gemm_mainloop<256>(acc, r, sbase, 10, wg, elect);
  const uint32_t stg = sbase + B_STG + wg * 16384;
  const int row0 = (ct >> 4) * SEQ + rb * 128 + wg * 64, col0 = (ct & 15) * 256;
  if (elect) tma_wait_read0();
  bar_sync(7 + wg, 128);
  store_tile128(acc, stg, &p.tmKV, col0, row0, wq, lane, wg, elect);
  if (elect) tma_wait_read0();
  bar_sync(7 + wg, 128);
  store_tile128(acc + 64, stg, &p.tmKV, col0 + 128, row0, wq, lane, wg, elect);
  if (elect) { tma_wait0(); fence_proxy_async(); __threadfence(); red_release(&g_f.kv[rb][ct], 1); }
}

__device__ __forceinline__ void task_gate(const Params& p, int rb) {
  const int tid = opaque_tid(), lane = tid & 31, warp = tid >> 5;
  uint2 gw[5];
#pragma unroll
  for (int k = 0; k < 5; k++) gw[k] = __ldg((const uint2*)(p.gate_w + (lane + 32 * k) * 4));
#pragma unroll 4
  for (int i = 0; i < 16; i++) {
    const int row = rb * 128 + warp * 16 + i;
    float s = 0.f;
#pragma unroll
    for (int k = 0; k < 5; k++) {
      uint2 xv = __ldg((const uint2*)(p.x + (size_t)row * DM + (lane + 32 * k) * 4));
      uint32_t m0 = pack_bf16(bflo(xv.x) * bflo(gw[k].x), bfhi(xv.x) * bfhi(gw[k].x));
      uint32_t m1 = pack_bf16(bflo(xv.y) * bflo(gw[k].y), bfhi(xv.y) * bfhi(gw[k].y));
      s += (bflo(m0) + bfhi(m0)) + (bflo(m1) + bfhi(m1));
    }
#pragma unroll
    for (int o = 16; o; o >>= 1) s += __shfl_xor_sync(0xffffffffu, s, o);
    if (lane == 0) { float z = bf16r(s); g_gate[row] = bf16r(1.0f / (1.0f + __expf(-z))); }
  }
  bar_sync(1, 256);
  if (tid == 0) { __threadfence(); red_release(&g_f.gate[rb], 1); }
}

constexpr int CV_U = 0, CV_UCH = 39 * 144;
constexpr int CV_W = 8 * CV_UCH, CV_WCH = (2048 + 64) * 4;
template<int NT0>
__device__ __forceinline__ void conv_block(float (&acc)[4][4][4], uint32_t (&e)[15], const uint32_t ub, const uint32_t wb) {
#pragma unroll 1
  for (int mm = 0; mm < 8; mm++) {
    const int m = NT0 * 8 + mm;
#pragma unroll
    for (int i = 0; i < 7; i++) e[i] = e[i + 8];
#pragma unroll
    for (int i = 7; i < 15; i++) e[i] = lds32(wb + (8 * m + i - 7) * 32);
#pragma unroll
    for (int nt = NT0; nt < 4; nt++) {
      uint32_t b0[4], b1[4];
      const uint32_t ba = ub + (8 * nt - m) * 144;
      ldsm4(b0, ba); ldsm4(b1, ba + 64);
#pragma unroll
      for (int ks = 0; ks < 4; ks++) {
        const uint32_t x0 = ks < 2 ? b0[(ks & 1) * 2] : b1[(ks & 1) * 2], x1 = ks < 2 ? b0[(ks & 1) * 2 + 1] : b1[(ks & 1) * 2 + 1];
#pragma unroll
        for (int mt = 0; mt < 4; mt++) {
          const int c = 2 * (mt - ks) + 7;
          mma16816_4(acc[mt][nt], e[c], e[c + 1], e[c - 1], e[c], x0, x1);
        }
      }
    }
  }
}

__device__ __forceinline__ void task_conv(const Params& p, const uint32_t sbase, int ci) {
  const int tid = opaque_tid(), lane = tid & 31, warp = tid >> 5;
  const int d0 = ci * 8;
  for (int i = tid; i < 8 * 63; i += 256) { const int ch = i / 63, o = i - ch * 63; sts128(sbase + CV_U + ch * CV_UCH + o * 16, 0, 0, 0, 0); }
  {
    float sk[4][8];
#pragma unroll
    for (int c = 0; c < 8; c++) { uint2 v = __ldg((const uint2*)(p.shift_k + (d0 + c) * 4)); sk[0][c] = bflo(v.x); sk[1][c] = bfhi(v.x); sk[2][c] = bflo(v.y); sk[3][c] = bfhi(v.y); }
#pragma unroll 2
    for (int t = tid; t < SEQ; t += 256) {
      uint4 kk[4];
#pragma unroll
      for (int q = 0; q < 4; q++) kk[q] = (t - 3 + q >= 0) ? __ldg((const uint4*)(p.bk + (size_t)(t - 3 + q) * DM + d0)) : make_uint4(0, 0, 0, 0);
      const uint4 vv = __ldg((const uint4*)(p.bv + (size_t)t * DM + d0));
      const uint32_t ua = sbase + CV_U + ((t >> 6) + 7) * 144 + (t & 63) * 2;
#pragma unroll
      for (int c2 = 0; c2 < 4; c2++) {
        uint32_t s = 0;
#pragma unroll
        for (int q = 0; q < 4; q++) {
          const uint32_t kw = c2 == 0 ? kk[q].x : c2 == 1 ? kk[q].y : c2 == 2 ? kk[q].z : kk[q].w;
          const uint32_t pr = pack_bf16(bflo(kw) * sk[3 - q][2 * c2], bfhi(kw) * sk[3 - q][2 * c2 + 1]);
          s = q == 0 ? pr : pack_bf16(bflo(s) + bflo(pr), bfhi(s) + bfhi(pr));
        }
        const uint32_t vw = c2 == 0 ? vv.x : c2 == 1 ? vv.y : c2 == 2 ? vv.z : vv.w;
        const uint32_t kv = pack_bf16(bflo(s) * bflo(vw), bfhi(s) * bfhi(vw));
        sts16(ua + (2 * c2) * CV_UCH, kv & 0xffff); sts16(ua + (2 * c2 + 1) * CV_UCH, kv >> 16);
      }
    }
  }
  {
    const uint32_t wb = sbase + CV_W + warp * CV_WCH;
    if (lane < 16) sts128(wb + lane * 16, 0, 0, 0, 0);
    const bf16* kf = p.ssm_k + (size_t)(d0 + warp) * SEQ;
#pragma unroll 2
    for (int i = lane; i < 256; i += 32) {
      const uint4 v = __ldg((const uint4*)(kf + i * 8));
      const uint32_t prev = i ? (uint32_t)__ldg((const unsigned short*)(kf + i * 8 - 1)) : 0u;
      const uint32_t a = wb + (64 + i * 8) * 4;
      sts128(a, (v.x & 0xffff) | (prev << 16), __byte_perm(v.x, v.x, 0x1032), __byte_perm(v.y, v.x, 0x7610), __byte_perm(v.y, v.y, 0x1032));
      sts128(a + 16, __byte_perm(v.z, v.y, 0x7610), __byte_perm(v.z, v.z, 0x1032), __byte_perm(v.w, v.z, 0x7610), __byte_perm(v.w, v.w, 0x1032));
    }
  }
  bar_sync(1, 256);
  {
    const int g = lane >> 2, c4 = lane & 3;
    float acc[4][4][4];
#pragma unroll
    for (int a = 0; a < 4; a++)
#pragma unroll
      for (int b = 0; b < 4; b++) acc[a][b][0] = acc[a][b][1] = acc[a][b][2] = acc[a][b][3] = 0.f;
    const uint32_t wb = sbase + CV_W + warp * CV_WCH + (64 + g - 2 * c4) * 4;
    const uint32_t ub = sbase + CV_U + warp * CV_UCH + (7 + (lane & 7)) * 144 + (lane >> 3) * 16;
    uint32_t e[15];
#pragma unroll
    for (int i = 8; i < 15; i++) e[i] = lds32(wb + (i - 15) * 32);
    conv_block<0>(acc, e, ub, wb);
    conv_block<1>(acc, e, ub, wb);
    conv_block<2>(acc, e, ub, wb);
    conv_block<3>(acc, e, ub, wb);
    __syncwarp();
    const uint32_t yb = sbase + CV_W + warp * CV_WCH;
#pragma unroll
    for (int mt = 0; mt < 4; mt++)
#pragma unroll
      for (int nt = 0; nt < 4; nt++) {
        const uint32_t lo = pack_bf16(acc[mt][nt][0], acc[mt][nt][1]), hi = pack_bf16(acc[mt][nt][2], acc[mt][nt][3]);
        const int t0 = 64 * (8 * nt + 2 * c4) + 16 * mt + g;
        sts16(yb + t0 * 2, lo & 0xffff); sts16(yb + (t0 + 64) * 2, lo >> 16);
        sts16(yb + (t0 + 8) * 2, hi & 0xffff); sts16(yb + (t0 + 72) * 2, hi >> 16);
      }
  }
  bar_sync(1, 256);
  {
    const uint4 dv = __ldg((const uint4*)(p.ssm_D + d0));
#pragma unroll 2
    for (int t = tid; t < SEQ; t += 256) {
      const uint4 xv = __ldg((const uint4*)(p.x + (size_t)t * DM + d0));
      const uint32_t ua = sbase + CV_U + ((t >> 6) + 7) * 144 + (t & 63) * 2, ya = sbase + CV_W + t * 2;
      uint32_t o[4];
#pragma unroll
      for (int c2 = 0; c2 < 4; c2++) {
        const uint32_t kv0 = lds16(ua + (2 * c2) * CV_UCH), kv1 = lds16(ua + (2 * c2 + 1) * CV_UCH);
        const uint32_t y0 = lds16(ya + (2 * c2) * CV_WCH), y1 = lds16(ya + (2 * c2 + 1) * CV_WCH);
        const uint32_t dw = c2 == 0 ? dv.x : c2 == 1 ? dv.y : c2 == 2 ? dv.z : dv.w;
        const uint32_t xw = c2 == 0 ? xv.x : c2 == 1 ? xv.y : c2 == 2 ? xv.z : xv.w;
        const uint32_t kd = pack_bf16(bflo(kv0) * bflo(dw), bflo(kv1) * bfhi(dw));
        const uint32_t yy = pack_bf16(bflo(y0) + bflo(kd), bflo(y1) + bfhi(kd));
        o[c2] = pack_bf16(bflo(xw) * bflo(yy), bfhi(xw) * bfhi(yy));
      }
      *(uint4*)(&g_B[t][d0]) = make_uint4(o[0], o[1], o[2], o[3]);
    }
  }
  fence_proxy_async();
  bar_sync(1, 256);
  if (tid == 0) { __threadfence(); red_release(&g_f.conv[d0 >> 7], 1); }
}

__device__ __forceinline__ void task_qa(const Params& p, Ring& r, const uint32_t sbase, int rb, int h) {
  const int tid = opaque_tid(), lane = tid & 31, wg = tid >> 7, wq = (tid >> 5) & 3, warp = tid >> 5;
  const bool elect = (tid & 127) == 0;
  const uint32_t bb = sbase + B_BAR;
  const int g = lane >> 2, c4 = lane & 3;
  float acc[64];
  gemm_mainloop<128>(acc, r, sbase, 10, wg, elect);
  uint32_t qa[8][4];
#pragma unroll
  for (int ks = 0; ks < 8; ks++) {
    qa[ks][0] = pack_bf16(acc[ks * 8 + 0], acc[ks * 8 + 1]); qa[ks][1] = pack_bf16(acc[ks * 8 + 2], acc[ks * 8 + 3]);
    qa[ks][2] = pack_bf16(acc[ks * 8 + 4], acc[ks * 8 + 5]); qa[ks][3] = pack_bf16(acc[ks * 8 + 6], acc[ks * 8 + 7]);
  }
  const int seg = warp >> 1, half = warp & 1;
  float sc[5][4];
#pragma unroll
  for (int t = 0; t < 5; t++) sc[t][0] = sc[t][1] = sc[t][2] = sc[t][3] = 0.f;
  {
    mbar_wait(bb + BR_FULL + 8 * r.st, r.ph);
    const uint32_t sa = sbase + r.st * STAGE;
    const int rr = lane & 7, i = lane >> 3;
#pragma unroll
    for (int ks = 0; ks < 8; ks++) {
      const int eh = ks >> 2, chunk = (ks & 3) * 2 + (i & 1);
      uint32_t kx[4];
      ldsm4(kx, sa + eh * 16384 + (seg * 32 + (i >> 1) * 8 + rr) * 128 + ((chunk ^ rr) << 4));
      mma16816(sc[1], qa[ks], kx[0], kx[1]);
      mma16816(sc[2], qa[ks], kx[2], kx[3]);
      if (half) {
        ldsm4(kx, sa + eh * 16384 + (seg * 32 + 16 + (i >> 1) * 8 + rr) * 128 + ((chunk ^ rr) << 4));
        mma16816(sc[3], qa[ks], kx[0], kx[1]);
        mma16816(sc[4], qa[ks], kx[2], kx[3]);
      }
      if ((ks & 1) == 0) {
        const int ch2 = (ks & 3) * 2 + i;
        ldsm4(kx, sa + 32768 + eh * 4096 + (seg * 8 + rr) * 128 + ((ch2 ^ rr) << 4));
        mma16816(sc[0], qa[ks], kx[0], kx[1]);
        mma16816(sc[0], qa[ks + 1], kx[2], kx[3]);
      }
    }
    __syncwarp();
    bar_sync(7 + wg, 128);
    if (elect) mbar_arrive(bb + BR_EMPTY + 8 * r.st);
    r.next();
  }
  uint32_t pa[5][2];
  {
    const float scale = 0.08838834764831845f, L2E = 1.4426950408889634f;
#pragma unroll
    for (int rh = 0; rh < 2; rh++) {
      const int row = half * 16 + rh * 8 + g;
      float v[10];
#pragma unroll
      for (int t = 0; t < 5; t++) {
        uint32_t pk = pack_bf16(sc[t][rh * 2], sc[t][rh * 2 + 1]);
        pk = pack_bf16(bflo(pk) * scale, bfhi(pk) * scale);
        v[2 * t] = bflo(pk); v[2 * t + 1] = bfhi(pk);
        if (t > 0) { const int key = (t - 1) * 8 + 2 * c4; if (key > row) v[2 * t] = -1e9f; if (key + 1 > row) v[2 * t + 1] = -1e9f; }
      }
      float mx = v[0];
#pragma unroll
      for (int i = 1; i < 10; i++) mx = fmaxf(mx, v[i]);
      mx = fmaxf(mx, __shfl_xor_sync(0xffffffffu, mx, 1)); mx = fmaxf(mx, __shfl_xor_sync(0xffffffffu, mx, 2));
      float sum = 0.f;
#pragma unroll
      for (int i = 0; i < 10; i++) { v[i] = ex2((v[i] - mx) * L2E); sum += v[i]; }
      sum += __shfl_xor_sync(0xffffffffu, sum, 1); sum += __shfl_xor_sync(0xffffffffu, sum, 2);
      const float inv = rcp(sum);
#pragma unroll
      for (int t = 0; t < 5; t++) pa[t][rh] = pack_bf16(v[2 * t] * inv, v[2 * t + 1] * inv);
    }
  }
#pragma unroll
  for (int i = 0; i < 64; i++) acc[i] = 0.f;
  {
    mbar_wait(bb + BR_FULL + 8 * r.st, r.ph);
    const uint32_t sa = sbase + r.st * STAGE;
    const int rr = lane & 7, i = lane >> 3;
#pragma unroll
    for (int np = 0; np < 8; np++) {
      const int eh = np >> 2, chunk = (np & 3) * 2 + (i >> 1);
      uint32_t vx[4];
      ldsm4t(vx, sa + eh * 16384 + (seg * 32 + (i & 1) * 8 + rr) * 128 + ((chunk ^ rr) << 4));
      mma16816_4(acc + np * 8, pa[1][0], pa[1][1], pa[2][0], pa[2][1], vx[0], vx[1]);
      mma16816_4(acc + np * 8 + 4, pa[1][0], pa[1][1], pa[2][0], pa[2][1], vx[2], vx[3]);
      if (half) {
        ldsm4t(vx, sa + eh * 16384 + (seg * 32 + 16 + (i & 1) * 8 + rr) * 128 + ((chunk ^ rr) << 4));
        mma16816_4(acc + np * 8, pa[3][0], pa[3][1], pa[4][0], pa[4][1], vx[0], vx[1]);
        mma16816_4(acc + np * 8 + 4, pa[3][0], pa[3][1], pa[4][0], pa[4][1], vx[2], vx[3]);
      }
      if ((np & 1) == 0) {
        const int ch2 = (np & 3) * 2 + i;
        ldsm4t(vx, sa + 32768 + eh * 4096 + (seg * 8 + rr) * 128 + ((ch2 ^ rr) << 4));
        mma1688(acc + np * 8, pa[0][0], pa[0][1], vx[0]);
        mma1688(acc + np * 8 + 4, pa[0][0], pa[0][1], vx[1]);
        mma1688(acc + np * 8 + 8, pa[0][0], pa[0][1], vx[2]);
        mma1688(acc + np * 8 + 12, pa[0][0], pa[0][1], vx[3]);
      }
    }
    if (elect) tma_wait_read0();
    bar_sync(7 + wg, 128);
    if (elect) mbar_arrive(bb + BR_EMPTY + 8 * r.st);
    r.next();
  }
  store_tile128(acc, sbase + B_STG + wg * 16384, &p.tmO, h * 128, rb * 128 + wg * 64, wq, lane, wg, elect);
  if (elect) { tma_wait0(); fence_proxy_async(); __threadfence(); red_release(&g_f.o_rdy[rb][h >> 3], 1); }
}

__device__ __forceinline__ void task_op(const Params& p, Ring& r, const uint32_t sbase, int rb, int ct, int kc) {
  const int tid = opaque_tid(), lane = tid & 31, wg = tid >> 7, wq = (tid >> 5) & 3;
  const bool elect = (tid & 127) == 0;
  const int g = lane >> 2, c4 = lane & 3;
  float acc[64];
  gemm_mainloop<128>(acc, r, sbase, 16, wg, elect);
  const int row0 = rb * 128 + wg * 64 + wq * 16 + g, col0 = ct * 128 + 2 * c4;
#pragma unroll
  for (int j = 0; j < 16; j++) {
    __stcg((float2*)&g_P[kc][row0][col0 + j * 8], make_float2(acc[j * 4], acc[j * 4 + 1]));
    __stcg((float2*)&g_P[kc][row0 + 8][col0 + j * 8], make_float2(acc[j * 4 + 2], acc[j * 4 + 3]));
  }
  bar_sync(1, 256);
  if (tid == 0) {
    __threadfence();
    uint32_t tk = atomicAdd(&g_f.op_cnt[rb][ct], 1u);
    if (tk == 3) { __threadfence(); wait_flag(&g_f.conv[ct], 16); wait_flag(&g_f.gate[rb], 1); }
    sts32(sbase + B_BAR + BR_MISC, tk);
  }
  bar_sync(1, 256);
  if (lds32(sbase + B_BAR + BR_MISC) == 3) {
#pragma unroll
    for (int hf = 0; hf < 2; hf++) {
      const int row = row0 + hf * 8;
      const float gt = __ldcg(&g_gate[row]);
      const float og = bf16r(1.0f - gt);
#pragma unroll 4
      for (int j = 0; j < 16; j++) {
        float2 s = __ldcg((const float2*)&g_P[0][row][col0 + j * 8]);
#pragma unroll
        for (int q = 1; q < 4; q++) { float2 u = __ldcg((const float2*)&g_P[q][row][col0 + j * 8]); s.x += u.x; s.y += u.y; }
        const uint32_t av = pack_bf16(s.x, s.y);
        const uint32_t bv = __ldcg((const uint32_t*)&g_B[row][col0 + j * 8]);
        const uint32_t ga = pack_bf16(gt * bflo(av), gt * bfhi(av)), gb = pack_bf16(og * bflo(bv), og * bfhi(bv));
        *(uint32_t*)(p.out + (size_t)row * DM + col0 + j * 8) = pack_bf16(bflo(ga) + bflo(gb), bfhi(ga) + bfhi(gb));
      }
    }
  }
}

__device__ __forceinline__ void bulk_consumer(const Params& p, const uint32_t sbase) {
  Ring r{0, 0};
  const uint32_t bb = sbase + B_BAR;
  for (int it = 0;; it++) {
    const int slot = it & 1;
    mbar_wait(bb + BR_TQF + 8 * slot, (it >> 1) & 1);
    const int t = (int)lds32(bb + BR_TASK + 4 * slot);
    if (t >= N_TASKS) break;
    if (t < N_KV) task_kv(p, r, sbase, t);
    else if (t < T_CONV) task_gate(p, t - T_GATE);
    else if (t < T_RB) task_conv(p, sbase, t - T_CONV);
    else {
      const int rb = (t - T_RB) / N_RB, q = (t - T_RB) - rb * N_RB;
      if (q < 32) task_qa(p, r, sbase, rb, q);
      else task_op(p, r, sbase, rb, (q - 32) >> 2, (q - 32) & 3);
    }
    bar_sync(7 + (threadIdx.x >> 7), 128);
    if ((threadIdx.x & 127) == 0) mbar_arrive(bb + BR_TQE + 8 * slot);
  }
}

__global__ void __cluster_dims__(2, 1, 1) __launch_bounds__(384, 1) mega_kernel(const __grid_constant__ Params p) {
  extern __shared__ __align__(1024) unsigned char sm[];
  const int tid = threadIdx.x, warp = tid >> 5;
  const uint32_t sbase = smem_u32(sm);
  const uint32_t bb = sbase + B_BAR;
  const bool is_chain = p.do_chain && blockIdx.x < 64;
  if (tid == 0) {
    for (int i = 0; i < NST; i++) { mbar_init(bb + BR_FULL + 8 * i, 1); mbar_init(bb + BR_EMPTY + 8 * i, 2); }
    for (int i = 0; i < 2; i++) { mbar_init(bb + BR_TQF + 8 * i, 1); mbar_init(bb + BR_TQE + 8 * i, 2); mbar_init(bb + BR_KVF + 8 * i, 32); mbar_init(bb + BR_KVE + 8 * i, 8); }
    mbar_init(bb + BR_X, 1); mbar_init(bb + BR_PUB, 8);
    asm volatile("fence.mbarrier_init.release.cluster;" ::: "memory");
  }
  __syncthreads();
  cluster_sync_all();
  if (warp >= 8) {
    asm volatile("setmaxnreg.dec.sync.aligned.u32 40;");
    if (warp == 8) {
      if (is_chain) { chain_producer(sbase); bar_sync(2, 288); }
      if (tid == 256) bulk_producer(p, sbase);
    }
  } else {
    asm volatile("setmaxnreg.inc.sync.aligned.u32 232;");
    if (is_chain) { chain_consumer(p, sm, sbase); fence_proxy_async(); bar_sync(2, 288); }
    bulk_consumer(p, sbase);
    if (tid == 0 && p.do_reset) {
      __threadfence();
      if (atomicAdd(&g_f.exit_ctr, 1u) == gridDim.x - 1) {
        uint32_t* f = (uint32_t*)&g_f;
        for (int i = 0; i < (int)(sizeof(Flags) / 4); i++) f[i] = 0;
        __threadfence();
      }
    }
  }
}

typedef CUresult (*EncFn)(CUtensorMap*, CUtensorMapDataType, cuuint32_t, void*, const cuuint64_t*, const cuuint64_t*, const cuuint32_t*, const cuuint32_t*,
                          CUtensorMapInterleave, CUtensorMapSwizzle, CUtensorMapL2promotion, CUtensorMapFloatOOBfill);
static void make_map(EncFn enc, CUtensorMap* m, const void* base, uint64_t inner, uint64_t outer, uint32_t box_in, uint32_t box_out) {
  cuuint64_t dims[2] = {inner, outer}; cuuint64_t strides[1] = {inner * 2};
  cuuint32_t box[2] = {box_in, box_out}; cuuint32_t es[2] = {1, 1};
  enc(m, CU_TENSOR_MAP_DATA_TYPE_BFLOAT16, 2, (void*)base, dims, strides, box, es, CU_TENSOR_MAP_INTERLEAVE_NONE, CU_TENSOR_MAP_SWIZZLE_128B,
      CU_TENSOR_MAP_L2_PROMOTION_L2_256B, CU_TENSOR_MAP_FLOAT_OOB_FILL_NONE);
}
static void fill_params(Params& p, void* const* d_in, void* d_out) {
  static EncFn enc = nullptr;
  if (!enc) {
    void* fn = nullptr; cudaDriverEntryPointQueryResult qr;
    cudaGetDriverEntryPoint("cuTensorMapEncodeTiled", &fn, cudaEnableDefault, &qr);
    enc = (EncFn)fn;
    cudaFuncSetAttribute(mega_kernel, cudaFuncAttributeMaxDynamicSharedMemorySize, SMEM_TOTAL);
  }
  void *kv, *kvm, *o;
  cudaGetSymbolAddress(&kv, g_KV); cudaGetSymbolAddress(&kvm, g_KVm); cudaGetSymbolAddress(&o, g_O);
  p.x = (const bf16*)d_in[0]; p.mem0 = (const bf16*)d_in[1]; p.Wq = (const bf16*)d_in[2]; p.Wk = (const bf16*)d_in[3];
  p.Wv = (const bf16*)d_in[4]; p.Wo = (const bf16*)d_in[5];
  p.bk = (const bf16*)d_in[8]; p.bv = (const bf16*)d_in[9]; p.shift_k = (const bf16*)d_in[10]; p.ssm_k = (const bf16*)d_in[11];
  p.ssm_D = (const bf16*)d_in[12]; p.gate_w = (const bf16*)d_in[13];
  p.out = (bf16*)d_out;
  make_map(enc, &p.tmX, p.x, DM, SEQ, 64, 64);
  make_map(enc, &p.tmO, o, HD, SEQ, 64, 64);
  make_map(enc, &p.tmKV, kv, HD, 2 * SEQ, 64, 64);
  make_map(enc, &p.tmKVm, kvm, HD, 2 * NSEG * NM, 64, 32);
  make_map(enc, &p.tmWq, p.Wq, HD, DM, 64, 64);
  make_map(enc, &p.tmWk, p.Wk, HD, DM, 64, 64);
  make_map(enc, &p.tmWv, p.Wv, HD, DM, 64, 64);
  make_map(enc, &p.tmWo, p.Wo, DM, HD, 64, 64);
  p.dG = 1000; p.dG2 = 2200;
  p.t_begin = 0; p.t_end = N_TASKS; p.do_chain = 1; p.do_reset = 1;
}

extern "C" void kernel_launch(void* const* d_in, const int* in_sizes, int n_in, void* d_out, int out_size) {
  Params p;
  fill_params(p, d_in, d_out);
  mega_kernel<<<132, 384, SMEM_TOTAL>>>(p);
}
```

```cpp
#include <cuda_runtime.h>
#include <cuda_bf16.h>
#include <cuda.h>
#include <stdint.h>
#include <stddef.h>

typedef __nv_bfloat16 bf16;
constexpr int SEQ = 2048, DM = 640, NH = 32, DH = 128, NM = 8, SEG = 32, NSEG = 64, HD = 4096;

__device__ __forceinline__ uint32_t smem_u32(const void* p) { return (uint32_t)__cvta_generic_to_shared(p); }
__device__ __forceinline__ uint32_t mapa(uint32_t a, uint32_t r) { uint32_t d; asm volatile("mapa.shared::cluster.u32 %0, %1, %2;" : "=r"(d) : "r"(a), "r"(r)); return d; }
__device__ __forceinline__ void mbar_init(uint32_t a, uint32_t c) { asm volatile("mbarrier.init.shared::cta.b64 [%0], %1;" :: "r"(a), "r"(c) : "memory"); }
__device__ __forceinline__ void mbar_expect_tx(uint32_t a, uint32_t tx) { asm volatile("mbarrier.arrive.expect_tx.shared::cta.b64 _, [%0], %1;" :: "r"(a), "r"(tx) : "memory"); }
__device__ __forceinline__ void mbar_arrive(uint32_t a) { asm volatile("mbarrier.arrive.shared::cta.b64 _, [%0];" :: "r"(a) : "memory"); }
__device__ __forceinline__ bool mbar_try(uint32_t a, uint32_t ph) {
  uint32_t ok; asm volatile("{ .reg .pred p; mbarrier.try_wait.parity.shared::cta.b64 p, [%1], %2; selp.u32 %0, 1, 0, p; }" : "=r"(ok) : "r"(a), "r"(ph) : "memory"); return ok; }
__device__ int g_err;
__device__ __forceinline__ bool expired(uint32_t blk) {
  uint32_t t, d; asm volatile("mov.u32 %0, %%globaltimer_lo;" : "=r"(t)); asm volatile("ld.shared.u32 %0, [%1+1016];" : "=r"(d) : "r"(blk));
  return (int)(t - d) > 0; }
__device__ __forceinline__ int opaque_tid() { int t; asm volatile("mov.u32 %0, %%tid.x;" : "=r"(t)); return t; }
template<int ROLE = 0> __device__ __forceinline__ void mbar_wait(uint32_t a, uint32_t ph) {
  asm volatile("{\n .reg .pred p;\n .reg .u32 t, d;\n"
    "W: mbarrier.try_wait.parity.shared::cta.b64 p, [%0], %1;\n @p bra D;\n"
    " mov.u32 t, %%globaltimer_lo;\n and.b32 d, %0, 0xFFFFFC00;\n ld.shared.u32 d, [d+1016];\n sub.u32 t, t, d;\n setp.le.s32 p, t, 0;\n @p bra W;\n"
    "D:\n }" :: "r"(a), "r"(ph) : "memory"); }
__device__ __forceinline__ void st_async_v2(uint32_t addr, uint32_t x, uint32_t y, uint32_t mbar) {
  asm volatile("st.async.weak.shared::cluster.mbarrier::complete_tx::bytes.v2.b32 [%0], {%1,%2}, [%3];" :: "r"(addr), "r"(x), "r"(y), "r"(mbar) : "memory"); }
__device__ __forceinline__ void cluster_sync_all() { asm volatile("barrier.cluster.arrive.release.aligned; barrier.cluster.wait.acquire.aligned;" ::: "memory"); }
__device__ __forceinline__ void bar_sync(int id, int n) { asm volatile("bar.sync %0, %1;" :: "r"(id), "r"(n) : "memory"); }
__device__ __forceinline__ void bar_arrive(int id, int n) { asm volatile("bar.arrive %0, %1;" :: "r"(id), "r"(n) : "memory"); }
__device__ __forceinline__ uint4 ld_relaxed_v4(const uint32_t* p) { uint4 v; asm volatile("ld.relaxed.gpu.global.v4.u32 {%0,%1,%2,%3}, [%4];" : "=r"(v.x), "=r"(v.y), "=r"(v.z), "=r"(v.w) : "l"(p) : "memory"); return v; }
__device__ __forceinline__ void st_relaxed_v4(uint32_t* p, uint32_t a, uint32_t b, uint32_t c, uint32_t d) { asm volatile("st.relaxed.gpu.global.v4.u32 [%0], {%1,%2,%3,%4};" :: "l"(p), "r"(a), "r"(b), "r"(c), "r"(d) : "memory"); }
__device__ __forceinline__ void st_relaxed(uint32_t* p, uint32_t v) { asm volatile("st.relaxed.gpu.global.u32 [%0], %1;" :: "l"(p), "r"(v) : "memory"); }
__device__ __forceinline__ uint32_t ld_acquire(const uint32_t* p) { uint32_t v; asm volatile("ld.acquire.gpu.global.u32 %0, [%1];" : "=r"(v) : "l"(p) : "memory"); return v; }
__device__ __forceinline__ void red_release(uint32_t* p, uint32_t v) { asm volatile("red.release.gpu.global.add.u32 [%0], %1;" :: "l"(p), "r"(v) : "memory"); }
__device__ __forceinline__ void st_release(uint32_t* p, uint32_t v) { asm volatile("st.release.gpu.global.u32 [%0], %1;" :: "l"(p), "r"(v) : "memory"); }
__device__ __forceinline__ void wait_flag(uint32_t blk, const uint32_t* p, uint32_t target) {
  while (ld_acquire(p) < target) { __nanosleep(64); if (expired(blk)) break; } }
__device__ __forceinline__ void fence_proxy_async() { asm volatile("fence.proxy.async;" ::: "memory"); }
__device__ __forceinline__ void fence_proxy_async_smem() { asm volatile("fence.proxy.async.shared::cta;" ::: "memory"); }
__device__ __forceinline__ void mma16816(float* d, const uint32_t* a, uint32_t b0, uint32_t b1) {
  asm volatile("mma.sync.aligned.m16n8k16.row.col.f32.bf16.bf16.f32 {%0,%1,%2,%3}, {%4,%5,%6,%7}, {%8,%9}, {%0,%1,%2,%3};"
    : "+f"(d[0]), "+f"(d[1]), "+f"(d[2]), "+f"(d[3]) : "r"(a[0]), "r"(a[1]), "r"(a[2]), "r"(a[3]), "r"(b0), "r"(b1)); }
__device__ __forceinline__ void mma16816_4(float* d, uint32_t a0, uint32_t a1, uint32_t a2, uint32_t a3, uint32_t b0, uint32_t b1) {
  asm volatile("mma.sync.aligned.m16n8k16.row.col.f32.bf16.bf16.f32 {%0,%1,%2,%3}, {%4,%5,%6,%7}, {%8,%9}, {%0,%1,%2,%3};"
    : "+f"(d[0]), "+f"(d[1]), "+f"(d[2]), "+f"(d[3]) : "r"(a0), "r"(a1), "r"(a2), "r"(a3), "r"(b0), "r"(b1)); }
__device__ __forceinline__ void mma1688(float* d, uint32_t a0, uint32_t a1, uint32_t b0) {
  asm volatile("mma.sync.aligned.m16n8k8.row.col.f32.bf16.bf16.f32 {%0,%1,%2,%3}, {%4,%5}, {%6}, {%0,%1,%2,%3};"
    : "+f"(d[0]), "+f"(d[1]), "+f"(d[2]), "+f"(d[3]) : "r"(a0), "r"(a1), "r"(b0)); }
__device__ __forceinline__ void ldsm4(uint32_t* r, uint32_t addr) { asm volatile("ldmatrix.sync.aligned.m8n8.x4.shared.b16 {%0,%1,%2,%3}, [%4];" : "=r"(r[0]), "=r"(r[1]), "=r"(r[2]), "=r"(r[3]) : "r"(addr) : "memory"); }
__device__ __forceinline__ void ldsm4t(uint32_t* r, uint32_t addr) { asm volatile("ldmatrix.sync.aligned.m8n8.x4.trans.shared.b16 {%0,%1,%2,%3}, [%4];" : "=r"(r[0]), "=r"(r[1]), "=r"(r[2]), "=r"(r[3]) : "r"(addr) : "memory"); }
__device__ __forceinline__ void stsm4(uint32_t addr, uint32_t a, uint32_t b, uint32_t c, uint32_t d) { asm volatile("stmatrix.sync.aligned.m8n8.x4.shared.b16 [%0], {%1,%2,%3,%4};" :: "r"(addr), "r"(a), "r"(b), "r"(c), "r"(d) : "memory"); }
__device__ __forceinline__ void stsm4t(uint32_t addr, uint32_t a, uint32_t b, uint32_t c, uint32_t d) { asm volatile("stmatrix.sync.aligned.m8n8.x4.trans.shared.b16 [%0], {%1,%2,%3,%4};" :: "r"(addr), "r"(a), "r"(b), "r"(c), "r"(d) : "memory"); }
__device__ __forceinline__ uint32_t movm(uint32_t a) { uint32_t d; asm volatile("movmatrix.sync.aligned.m8n8.trans.b16 %0, %1;" : "=r"(d) : "r"(a)); return d; }
__device__ __forceinline__ uint32_t pack_bf16(float lo, float hi) { uint32_t d; asm("cvt.rn.bf16x2.f32 %0, %1, %2;" : "=r"(d) : "f"(hi), "f"(lo)); return d; }
__device__ __forceinline__ uint32_t bmul2(uint32_t a, uint32_t b) { uint32_t d; asm("mul.rn.bf16x2 %0, %1, %2;" : "=r"(d) : "r"(a), "r"(b)); return d; }
__device__ __forceinline__ uint32_t badd2(uint32_t a, uint32_t b) { uint32_t d; asm("add.rn.bf16x2 %0, %1, %2;" : "=r"(d) : "r"(a), "r"(b)); return d; }
__device__ __forceinline__ float bf16r(float x) { return __uint_as_float(pack_bf16(0.f, x)); }
__device__ __forceinline__ float bflo(uint32_t v) { return __uint_as_float(v << 16); }
__device__ __forceinline__ float bfhi(uint32_t v) { return __uint_as_float(v & 0xffff0000u); }
__device__ __forceinline__ uint32_t clk32() { uint32_t c; asm volatile("mov.u32 %0, %%clock;" : "=r"(c)); return c; }
__device__ __forceinline__ void lds128(uint32_t* r, uint32_t a) { asm volatile("ld.shared.v4.b32 {%0,%1,%2,%3}, [%4];" : "=r"(r[0]), "=r"(r[1]), "=r"(r[2]), "=r"(r[3]) : "r"(a) : "memory"); }
__device__ __forceinline__ void lds64(uint32_t* r, uint32_t a) { asm volatile("ld.shared.v2.b32 {%0,%1}, [%2];" : "=r"(r[0]), "=r"(r[1]) : "r"(a) : "memory"); }
__device__ __forceinline__ uint32_t lds32(uint32_t a) { uint32_t r; asm volatile("ld.shared.b32 %0, [%1];" : "=r"(r) : "r"(a) : "memory"); return r; }
__device__ __forceinline__ uint32_t lds16(uint32_t a) { uint16_t r; asm volatile("ld.shared.u16 %0, [%1];" : "=h"(r) : "r"(a) : "memory"); return r; }
__device__ __forceinline__ void sts128(uint32_t a, uint32_t x, uint32_t y, uint32_t z, uint32_t w) { asm volatile("st.shared.v4.b32 [%0], {%1,%2,%3,%4};" :: "r"(a), "r"(x), "r"(y), "r"(z), "r"(w) : "memory"); }
__device__ __forceinline__ void sts64(uint32_t a, uint32_t x, uint32_t y) { asm volatile("st.shared.v2.b32 [%0], {%1,%2};" :: "r"(a), "r"(x), "r"(y) : "memory"); }
__device__ __forceinline__ void sts32(uint32_t a, uint32_t x) { asm volatile("st.shared.b32 [%0], %1;" :: "r"(a), "r"(x) : "memory"); }
__device__ __forceinline__ void sts16(uint32_t a, uint32_t x) { asm volatile("st.shared.u16 [%0], %1;" :: "r"(a), "h"((uint16_t)x) : "memory"); }
__device__ __forceinline__ float ex2(float x) { float y; asm("ex2.approx.ftz.f32 %0, %1;" : "=f"(y) : "f"(x)); return y; }
__device__ __forceinline__ float rcp(float x) { float y; asm("rcp.approx.ftz.f32 %0, %1;" : "=f"(y) : "f"(x)); return y; }
__device__ __forceinline__ void tma_load(uint32_t dst, const CUtensorMap* tm, int c0, int c1, uint32_t bar) {
  asm volatile("cp.async.bulk.tensor.2d.shared::cluster.global.mbarrier::complete_tx::bytes [%0], [%1, {%3, %4}], [%2];"
    :: "r"(dst), "l"((uint64_t)tm), "r"(bar), "r"(c0), "r"(c1) : "memory"); }
__device__ __forceinline__ void tma_load3(uint32_t dst, const CUtensorMap* tm, int c1, int c2, uint32_t bar) {
  asm volatile("cp.async.bulk.tensor.3d.shared::cluster.global.mbarrier::complete_tx::bytes [%0], [%1, {%3, %4, %5}], [%2];"
    :: "r"(dst), "l"((uint64_t)tm), "r"(bar), "r"(0), "r"(c1), "r"(c2) : "memory"); }
__device__ __forceinline__ void tma_store(const CUtensorMap* tm, uint32_t src, int c0, int c1) {
  asm volatile("cp.async.bulk.tensor.2d.global.shared::cta.bulk_group [%0, {%2, %3}], [%1];" :: "l"((uint64_t)tm), "r"(src), "r"(c0), "r"(c1) : "memory"); }
__device__ __forceinline__ void tma_commit() { asm volatile("cp.async.bulk.commit_group;" ::: "memory"); }
__device__ __forceinline__ void tma_wait_read0() { asm volatile("cp.async.bulk.wait_group.read 0;" ::: "memory"); }
__device__ __forceinline__ void tma_wait0() { asm volatile("cp.async.bulk.wait_group 0;" ::: "memory"); }
__device__ __forceinline__ void wg_fence() { asm volatile("wgmma.fence.sync.aligned;" ::: "memory"); }
__device__ __forceinline__ void wg_commit() { asm volatile("wgmma.commit_group.sync.aligned;" ::: "memory"); }
template<int N> __device__ __forceinline__ void wg_wait() { asm volatile("wgmma.wait_group.sync.aligned %0;" :: "n"(N) : "memory"); }
__device__ __forceinline__ uint64_t make_desc(uint32_t addr, uint32_t lbo, uint32_t sbo) {
  return (uint64_t)((addr & 0x3FFFF) >> 4) | ((uint64_t)(lbo >> 4) << 16) | ((uint64_t)(sbo >> 4) << 32) | (1ull << 62); }
__device__ __forceinline__ void wgmma_n128(float* d, uint64_t da, uint64_t db) {
  asm volatile("wgmma.mma_async.sync.aligned.m64n128k16.f32.bf16.bf16 {%0, %1, %2, %3, %4, %5, %6, %7, %8, %9, %10, %11, %12, %13, %14, %15, %16, %17, %18, %19, %20, %21, %22, %23, %24, %25, %26, %27, %28, %29, %30, %31, %32, %33, %34, %35, %36, %37, %38, %39, %40, %41, %42, %43, %44, %45, %46, %47, %48, %49, %50, %51, %52, %53, %54, %55, %56, %57, %58, %59, %60, %61, %62, %63}, %64, %65, 1, 1, 1, 0, 1;"
    : "+f"(d[0]), "+f"(d[1]), "+f"(d[2]), "+f"(d[3]), "+f"(d[4]), "+f"(d[5]), "+f"(d[6]), "+f"(d[7]), "+f"(d[8]), "+f"(d[9]), "+f"(d[10]), "+f"(d[11]), "+f"(d[12]), "+f"(d[13]), "+f"(d[14]), "+f"(d[15]), "+f"(d[16]), "+f"(d[17]), "+f"(d[18]), "+f"(d[19]), "+f"(d[20]), "+f"(d[21]), "+f"(d[22]), "+f"(d[23]), "+f"(d[24]), "+f"(d[25]), "+f"(d[26]), "+f"(d[27]), "+f"(d[28]), "+f"(d[29]), "+f"(d[30]), "+f"(d[31]), "+f"(d[32]), "+f"(d[33]), "+f"(d[34]), "+f"(d[35]), "+f"(d[36]), "+f"(d[37]), "+f"(d[38]), "+f"(d[39]), "+f"(d[40]), "+f"(d[41]), "+f"(d[42]), "+f"(d[43]), "+f"(d[44]), "+f"(d[45]), "+f"(d[46]), "+f"(d[47]), "+f"(d[48]), "+f"(d[49]), "+f"(d[50]), "+f"(d[51]), "+f"(d[52]), "+f"(d[53]), "+f"(d[54]), "+f"(d[55]), "+f"(d[56]), "+f"(d[57]), "+f"(d[58]), "+f"(d[59]), "+f"(d[60]), "+f"(d[61]), "+f"(d[62]), "+f"(d[63])
    : "l"(da), "l"(db));
}

__device__ __forceinline__ void wgmma_n192(float* d, uint64_t da, uint64_t db) {
  asm volatile("wgmma.mma_async.sync.aligned.m64n192k16.f32.bf16.bf16 {%0, %1, %2, %3, %4, %5, %6, %7, %8, %9, %10, %11, %12, %13, %14, %15, %16, %17, %18, %19, %20, %21, %22, %23, %24, %25, %26, %27, %28, %29, %30, %31, %32, %33, %34, %35, %36, %37, %38, %39, %40, %41, %42, %43, %44, %45, %46, %47, %48, %49, %50, %51, %52, %53, %54, %55, %56, %57, %58, %59, %60, %61, %62, %63, %64, %65, %66, %67, %68, %69, %70, %71, %72, %73, %74, %75, %76, %77, %78, %79, %80, %81, %82, %83, %84, %85, %86, %87, %88, %89, %90, %91, %92, %93, %94, %95}, %96, %97, 1, 1, 1, 0, 1;"
    : "+f"(d[0]), "+f"(d[1]), "+f"(d[2]), "+f"(d[3]), "+f"(d[4]), "+f"(d[5]), "+f"(d[6]), "+f"(d[7]), "+f"(d[8]), "+f"(d[9]), "+f"(d[10]), "+f"(d[11]), "+f"(d[12]), "+f"(d[13]), "+f"(d[14]), "+f"(d[15]), "+f"(d[16]), "+f"(d[17]), "+f"(d[18]), "+f"(d[19]), "+f"(d[20]), "+f"(d[21]), "+f"(d[22]), "+f"(d[23]), "+f"(d[24]), "+f"(d[25]), "+f"(d[26]), "+f"(d[27]), "+f"(d[28]), "+f"(d[29]), "+f"(d[30]), "+f"(d[31]), "+f"(d[32]), "+f"(d[33]), "+f"(d[34]), "+f"(d[35]), "+f"(d[36]), "+f"(d[37]), "+f"(d[38]), "+f"(d[39]), "+f"(d[40]), "+f"(d[41]), "+f"(d[42]), "+f"(d[43]), "+f"(d[44]), "+f"(d[45]), "+f"(d[46]), "+f"(d[47]), "+f"(d[48]), "+f"(d[49]), "+f"(d[50]), "+f"(d[51]), "+f"(d[52]), "+f"(d[53]), "+f"(d[54]), "+f"(d[55]), "+f"(d[56]), "+f"(d[57]), "+f"(d[58]), "+f"(d[59]), "+f"(d[60]), "+f"(d[61]), "+f"(d[62]), "+f"(d[63]), "+f"(d[64]), "+f"(d[65]), "+f"(d[66]), "+f"(d[67]), "+f"(d[68]), "+f"(d[69]), "+f"(d[70]), "+f"(d[71]), "+f"(d[72]), "+f"(d[73]), "+f"(d[74]), "+f"(d[75]), "+f"(d[76]), "+f"(d[77]), "+f"(d[78]), "+f"(d[79]), "+f"(d[80]), "+f"(d[81]), "+f"(d[82]), "+f"(d[83]), "+f"(d[84]), "+f"(d[85]), "+f"(d[86]), "+f"(d[87]), "+f"(d[88]), "+f"(d[89]), "+f"(d[90]), "+f"(d[91]), "+f"(d[92]), "+f"(d[93]), "+f"(d[94]), "+f"(d[95])
    : "l"(da), "l"(db));
}

__device__ __forceinline__ void wgmma_n256(float* d, uint64_t da, uint64_t db) {
  asm volatile("wgmma.mma_async.sync.aligned.m64n256k16.f32.bf16.bf16 {%0, %1, %2, %3, %4, %5, %6, %7, %8, %9, %10, %11, %12, %13, %14, %15, %16, %17, %18, %19, %20, %21, %22, %23, %24, %25, %26, %27, %28, %29, %30, %31, %32, %33, %34, %35, %36, %37, %38, %39, %40, %41, %42, %43, %44, %45, %46, %47, %48, %49, %50, %51, %52, %53, %54, %55, %56, %57, %58, %59, %60, %61, %62, %63, %64, %65, %66, %67, %68, %69, %70, %71, %72, %73, %74, %75, %76, %77, %78, %79, %80, %81, %82, %83, %84, %85, %86, %87, %88, %89, %90, %91, %92, %93, %94, %95, %96, %97, %98, %99, %100, %101, %102, %103, %104, %105, %106, %107, %108, %109, %110, %111, %112, %113, %114, %115, %116, %117, %118, %119, %120, %121, %122, %123, %124, %125, %126, %127}, %128, %129, 1, 1, 1, 0, 1;"
    : "+f"(d[0]), "+f"(d[1]), "+f"(d[2]), "+f"(d[3]), "+f"(d[4]), "+f"(d[5]), "+f"(d[6]), "+f"(d[7]), "+f"(d[8]), "+f"(d[9]), "+f"(d[10]), "+f"(d[11]), "+f"(d[12]), "+f"(d[13]), "+f"(d[14]), "+f"(d[15]), "+f"(d[16]), "+f"(d[17]), "+f"(d[18]), "+f"(d[19]), "+f"(d[20]), "+f"(d[21]), "+f"(d[22]), "+f"(d[23]), "+f"(d[24]), "+f"(d[25]), "+f"(d[26]), "+f"(d[27]), "+f"(d[28]), "+f"(d[29]), "+f"(d[30]), "+f"(d[31]), "+f"(d[32]), "+f"(d[33]), "+f"(d[34]), "+f"(d[35]), "+f"(d[36]), "+f"(d[37]), "+f"(d[38]), "+f"(d[39]), "+f"(d[40]), "+f"(d[41]), "+f"(d[42]), "+f"(d[43]), "+f"(d[44]), "+f"(d[45]), "+f"(d[46]), "+f"(d[47]), "+f"(d[48]), "+f"(d[49]), "+f"(d[50]), "+f"(d[51]), "+f"(d[52]), "+f"(d[53]), "+f"(d[54]), "+f"(d[55]), "+f"(d[56]), "+f"(d[57]), "+f"(d[58]), "+f"(d[59]), "+f"(d[60]), "+f"(d[61]), "+f"(d[62]), "+f"(d[63]), "+f"(d[64]), "+f"(d[65]), "+f"(d[66]), "+f"(d[67]), "+f"(d[68]), "+f"(d[69]), "+f"(d[70]), "+f"(d[71]), "+f"(d[72]), "+f"(d[73]), "+f"(d[74]), "+f"(d[75]), "+f"(d[76]), "+f"(d[77]), "+f"(d[78]), "+f"(d[79]), "+f"(d[80]), "+f"(d[81]), "+f"(d[82]), "+f"(d[83]), "+f"(d[84]), "+f"(d[85]), "+f"(d[86]), "+f"(d[87]), "+f"(d[88]), "+f"(d[89]), "+f"(d[90]), "+f"(d[91]), "+f"(d[92]), "+f"(d[93]), "+f"(d[94]), "+f"(d[95]), "+f"(d[96]), "+f"(d[97]), "+f"(d[98]), "+f"(d[99]), "+f"(d[100]), "+f"(d[101]), "+f"(d[102]), "+f"(d[103]), "+f"(d[104]), "+f"(d[105]), "+f"(d[106]), "+f"(d[107]), "+f"(d[108]), "+f"(d[109]), "+f"(d[110]), "+f"(d[111]), "+f"(d[112]), "+f"(d[113]), "+f"(d[114]), "+f"(d[115]), "+f"(d[116]), "+f"(d[117]), "+f"(d[118]), "+f"(d[119]), "+f"(d[120]), "+f"(d[121]), "+f"(d[122]), "+f"(d[123]), "+f"(d[124]), "+f"(d[125]), "+f"(d[126]), "+f"(d[127])
    : "l"(da), "l"(db));
}

__device__ __align__(1024) bf16 g_KV[2 * SEQ][HD];
__device__ __align__(1024) bf16 g_KVm[2 * NSEG * NM][HD];
__device__ __align__(1024) bf16 g_O[SEQ][HD];
__device__ __align__(1024) float g_P[8][SEQ][DM];
__device__ __align__(1024) bf16 g_B[SEQ][DM];
__device__ __align__(1024) bf16 g_kvT[DM][SEQ];
__device__ __align__(1024) bf16 g_ybT[DM][SEQ];
__device__ float g_gate[SEQ];
__device__ __align__(128) uint32_t g_part[2][64][32][80];
__device__ __align__(128) uint32_t g_memt[2][5120];
__device__ __align__(128) uint32_t g_mem[4][2560];
struct Flags {
  uint32_t task_ctr, exit_ctr, prep, conv, pad0[28];
  uint32_t kv[16][64];
  uint32_t prog[64][8];
  uint32_t o_rdy[16][8];
  uint32_t op_tk[16][2];
  uint32_t op_wr[16][2];
  uint32_t post[16];
};
__device__ __align__(128) Flags g_f;

struct Params {
  CUtensorMap tmX, tmO, tmKV, tmKVm, tmWq, tmWk, tmWv, tmWo, tmKT, tmYT, tmOl, tmKVl, tmW1[3], tmWo1;
  const bf16 *x, *mem0, *Wq, *Wk, *Wv, *Wo, *bk, *bv, *shift_k, *ssm_k, *ssm_D, *gate_w;
  bf16* out;
  int dG, dG2;
  int t_begin, t_end, do_chain, do_reset, do_kv;
};

constexpr int T_CONV = 16, T_QA0 = 96, T_POST = 128, T_G = 144, T_TAIL = T_G + 14 * 20, N_TASKS = T_TAIL + 32;
enum { K_PREP, K_CONV, K_POST, K_QA, K_OP };
__device__ __forceinline__ int decode(int t, int& rb, int& q, int& kcn) {
  kcn = 2; q = 0;
  if (t < T_CONV) { rb = t; return K_PREP; }
  if (t < T_QA0) { rb = 0; q = t - T_CONV; return K_CONV; }
  if (t < T_POST) { rb = (t - T_QA0) >> 4; q = t & 15; return K_QA; }
  if (t < T_G) { rb = t - T_POST; return K_POST; }
  if (t < T_TAIL) { const int g = (t - T_G) / 20; q = (t - T_G) - g * 20; if (q < 4) { rb = g; return K_OP; } q -= 4; rb = g + 2; return K_QA; }
  kcn = 8; rb = 14 + ((t - T_TAIL) >> 4); q = (t - T_TAIL) & 15; return K_OP;
}

constexpr int STAGE = 57344, NST = 3;
constexpr int B_STG = 196608;
constexpr int B_BAR = B_STG + 32768;
constexpr int SMEM_TOTAL = B_BAR + 1024;
constexpr int KV_X = 163840, KV_STG = KV_X + 3 * 16384;
constexpr int BR_FULL = 0, BR_EMPTY = 32, BR_TQF = 64, BR_TQE = 80, BR_TASK = 96, BR_X = 128, BR_KVF = 136, BR_KVE = 152, BR_MISC = 168,
              BR_SFREE = 176, BR_JOB = 192  , BR_WF = 256  , BR_XF = 336, BR_XE = 360, BR_CV = 384;

#define KR 12
#define WR 6
#define ADJ_DN 8
#define ADJ_UP 128
#define G2_TAGGED
#define G2_UNIT
constexpr int WF0 = 4;
#define NQA 9
template<int V> struct IC { static constexpr int value = V; };
constexpr int NSQ = (20 - KR) * 3;
constexpr int NSF_LO = NSQ + 24 - WR, NSF_HI = NSQ + 16 - WR;
constexpr int OFF_WF = 0;
constexpr int OFF_RT = OFF_WF + 4 * (NSF_LO + NSF_HI) * 512;
constexpr int OFF_MEMB = OFF_RT;
constexpr int OFF_RED = OFF_MEMB + 10240;
constexpr int OFF_SP = OFF_RED + 6144;
constexpr int OFF_SX = OFF_SP + 5120;
constexpr int OFF_VM = OFF_SX + 2560;
constexpr int OFF_O = OFF_VM + 2048;
constexpr int OFF_KX = OFF_O + 2048;
constexpr int OFF_VX = OFF_KX + 9216;
constexpr int OFF_CST = OFF_VX + 17408;
constexpr int OFF_RT_END = OFF_CST + 8192;
static_assert(WF0 + WR <= 16 && OFF_RT <= B_BAR && OFF_RT_END + 4096 <= B_BAR, "chain smem");
#define STAMP(i)

#define PST(i)
__device__ __forceinline__ void chain_prefetch(const uint32_t sbase, int s, int h, int j, int lane) {
  const int b = s & 1;
  if ((s & 3) == 0) {
    if (lane == 0) { wait_flag(sbase + B_BAR, &g_f.kv[s >> 2][h], 1); wait_flag(sbase + B_BAR, &g_f.kv[s >> 2][32 + h], 1); }
    __syncwarp();
  }
  const bf16* kp = &g_KV[s * SEG][h * DH + j * 64];
  const bf16* vp = &g_KV[SEQ + s * SEG][h * DH];
#pragma unroll 2
  for (int k = 0; k < 8; k++) { int c = lane + 32 * k;
    asm volatile("cp.async.cg.shared.global [%0], [%1], 16;" :: "r"(sbase + OFF_KX + b * 4608 + (c >> 3) * 144 + (c & 7) * 16), "l"(kp + (size_t)(c >> 3) * HD + (c & 7) * 8) : "memory"); }
#pragma unroll 2
  for (int k = 0; k < 16; k++) { int c = lane + 32 * k;
    asm volatile("cp.async.cg.shared.global [%0], [%1], 16;" :: "r"(sbase + OFF_VX + b * 8704 + (c >> 4) * 272 + (c & 15) * 16), "l"(vp + (size_t)(c >> 4) * HD + (c & 15) * 8) : "memory"); }
  asm volatile("cp.async.mbarrier.arrive.noinc.shared::cta.b64 [%0];" :: "r"(sbase + B_BAR + BR_KVF + 8 * b) : "memory");
}

__device__ __forceinline__ void chain_producer(const uint32_t sbase) {
  const int lane = threadIdx.x & 31;
  const int h = blockIdx.x >> 1, j = blockIdx.x & 1;
  bar_sync(2, 288);
  chain_prefetch(sbase, 0, h, j, lane);
  chain_prefetch(sbase, 1, h, j, lane);
  for (int s = 0; s < NSEG; s++) {
    mbar_wait<1>(sbase + B_BAR + BR_KVE + 8 * (s & 1), (s >> 1) & 1);
    if (s + 2 < NSEG) chain_prefetch(sbase, s + 2, h, j, lane);
    if ((s & 3) == 3) {
      if (s + 1 < NSEG) __nanosleep(600);
      if (lane == 0) { __threadfence(); st_release(&g_f.prog[blockIdx.x][0], s + 1); }
      __syncwarp();
    }
  }
}

__device__ __forceinline__ void chain_consumer(const Params& a, unsigned char* sm, const uint32_t sbase) {
    const int tid = opaque_tid(), lane = tid & 31, warp = tid >> 5;
    const int h = blockIdx.x >> 1, j = blockIdx.x & 1;
    const uint32_t bar_x = sbase + B_BAR + BR_X, bar_full = sbase + B_BAR + BR_KVF, bar_empty = sbase + B_BAR + BR_KVE;
    const int kg = warp >> 2, mg = warp & 3;
    uint32_t wA[KR * 3][4];
    uint32_t wO[WR][4];
    const uint32_t swf0 = sbase + OFF_WF + (warp < 4 ? warp * NSF_LO : 4 * NSF_LO + (warp - 4) * NSF_HI) * 512 + lane * 16;
    {
      static_assert(KR == 12 && 18 * 8192 <= OFF_RT && OFF_RT % 1024 == 0 && OFF_RT + 65536 <= B_BAR, "prologue staging");
      const uint32_t wb = sbase + B_BAR + BR_WF, ring = sbase + OFF_RT;
      const int li = lane >> 3, lr = lane & 7;
      auto piece = [&](int pc) {
        const uint32_t dst = ring + (pc & 1) * 32768, bar = wb + 24 + pc * 8;
        if (pc < 3) {
          mbar_expect_tx(bar, 32768);
#pragma unroll 1
          for (int q = 0; q < 4; q++) tma_load(dst + q * 8192, &a.tmW1[pc], h * DH + j * 64, 320 * (q >> 1) + 192 + (q & 1) * 64, bar);
        } else {
          mbar_expect_tx(bar, pc < 5 ? 32768 : 16384);
          tma_load(dst, &a.tmWo1, j * 320 + (pc - 3) * 128, h * DH, bar);
          if (pc < 5) tma_load(dst + 16384, &a.tmWo1, j * 320 + (pc - 3) * 128 + 64, h * DH, bar);
        }
      };
      PST(0);
      if (tid == 0) {
#pragma unroll 1
        for (int i = 0; i < 3; i++) {
          mbar_expect_tx(wb + i * 8, 49152);
#pragma unroll 1
          for (int q = 0; q < 6; q++) tma_load(sbase + (i * 6 + q) * 8192, &a.tmW1[q >> 1], h * DH + j * 64, 320 * (q & 1) + i * 64, wb + i * 8);
        }
        piece(0); piece(1);
      }
      PST(1);
      const uint32_t fo = ((li >> 1) * 8 + lr) * 128;
      const uint32_t qsw = fo + (((mg * 2 + (li & 1)) ^ lr) << 4);
#pragma unroll
      for (int i = 0; i < 3; i++) {
        mbar_wait(wb + i * 8, 0);
#pragma unroll
        for (int c = 0; c < 4; c++)
#pragma unroll
          for (int m = 0; m < 3; m++) ldsm4t(wA[(i * 4 + c) * 3 + m], sbase + (i * 6 + m * 2 + kg) * 8192 + c * 2048 + qsw);
      }
      bar_sync(1, 256);
      PST(3);
#pragma unroll 1
      for (int pc = 0; pc < 3; pc++) {
        mbar_wait(wb + 24 + pc * 8, 0);
#pragma unroll 2
        for (int c = 0; c < 8; c++) {
          uint32_t t[4]; ldsm4t(t, ring + (pc & 1) * 32768 + kg * 16384 + c * 2048 + qsw);
          sts128(swf0 + (c * 3 + pc) * 512, t[0], t[1], t[2], t[3]);
        }
        bar_sync(1, 256);
        if (tid == 0) { fence_proxy_async_smem(); piece(pc + 2); }
      }
      PST(4);
#pragma unroll
      for (int pc = 3; pc < 6; pc++) {
        constexpr int dummy = 0; (void)dummy;
        const int i = pc == 3 ? 1 : (pc == 4 ? 0 : 2);
        mbar_wait(wb + 24 + pc * 8, 0);
        if (pc < 5 || warp < 4) {
          const uint32_t src = ring + (pc & 1) * 32768 + (pc < 5 ? (warp >> 2) * 16384 : 0) + qsw;
#pragma unroll
          for (int ks = 0; ks < 8; ks++) {
            const int f = i * 8 + ks;
            if (f >= WF0 && f < WF0 + WR) ldsm4t(wO[f - WF0], src + ks * 2048);
            else { uint32_t t[4]; ldsm4t(t, src + ks * 2048); sts128(swf0 + (NSQ + (f < WF0 ? f : f - WR)) * 512, t[0], t[1], t[2], t[3]); }
          }
        }
        bar_sync(1, 256);
        if (pc == 3 && tid == 0) { fence_proxy_async_smem(); piece(5); }
      }
    }
    PST(5);
    bar_sync(2, 288);
    if (tid == 0) mbar_expect_tx(bar_x, 2304);
    const uint32_t peer_off = mapa(sbase, j ^ 1) - sbase;
    const float SL2E = 0.08838834764831845f * 1.4426950408889634f;
    const int rme = 32 * j + h;
    const int g = lane >> 2, c4 = lane & 3;
    uint32_t part_off[3];
#pragma unroll
    for (int i = 0; i < 3; i++) {
      const int t = i < 2 ? warp + 8 * i : 16 + (warp & 3);
      const int U = (20 * j + t) * 16 + c4 * 4 + (g >> 1);
      const int r = U / 10;
      part_off[i] = (r * 32 + h) * 80 + ((U - r * 10) * 2 + (g & 1)) * 4;
    }
    const int rch = 4 * (warp - 3) + (lane & 3);
    const uint32_t rsrc_off = (rme * 32 + (lane >> 2)) * 80 + rch * 4;
    uint32_t mdst;
    {
      mdst = (rme * 10 + (rch >> 1)) * 8 + ((lane >> 3) & 1) * 4 + ((lane >> 4) & 1) * 2 + (rch & 1);
    }
    const uint32_t kvm_off = ((kg ? NSEG * NM : 0) + g) * HD + h * DH + j * 64 + mg * 16 + 2 * c4;
    const uint32_t l16 = sbase + lane * 16;
    const uint32_t cst = l16 + OFF_CST + warp * 1024;
    sts128(cst, part_off[1], part_off[0], part_off[2], rsrc_off);
    sts128(cst + 512, mdst, kvm_off, a.dG, a.dG2);
    const uint32_t swf = swf0;
    const uint32_t mb_dst = l16 + OFF_MEMB + (kg * 10 + (mg >> 1)) * 512 + (mg & 1) * 8;
    uint32_t Q[6][4];
#pragma unroll
    for (int k = 0; k < 5; k++) {
      const int ks = kg * 20 + mg + 4 * k;
      uint32_t b0 = *(const uint32_t*)(a.mem0 + g * DM + ks * 16 + 2 * c4), b1 = *(const uint32_t*)(a.mem0 + g * DM + ks * 16 + 8 + 2 * c4);
      sts64(mb_dst + k * 1024, b0, b1);
    }
#pragma unroll
    for (int n = 0; n < 6; n++) lds128(Q[n], swf + n * 512);
    mbar_wait(bar_full, 0);
    int tid_keep = tid;
#pragma unroll 1
    for (int s = 0; s < NSEG; s++) {
      const int b = s & 1;
      asm volatile("" : "+r"(tid_keep));
      const int tid = tid_keep, lane = tid & 31, warp = tid >> 5, kg = warp >> 2, mg = warp & 3;
      const uint32_t l8 = sbase + lane * 8, l16 = sbase + lane * 16;
      const uint32_t cst = l16 + OFF_CST + warp * 1024;
      const uint32_t swf = l16 + OFF_WF + (warp < 4 ? warp * NSF_LO : 4 * NSF_LO + (warp - 4) * NSF_HI) * 512;
      bar_sync(9 + kg, 128);
      STAMP(1);
      float acc[3][4];
#pragma unroll
      for (int m = 0; m < 3; m++) { acc[m][0] = acc[m][1] = acc[m][2] = acc[m][3] = 0.f; }
      {
        const uint32_t bb = l16 + OFF_MEMB + kg * 5120;
        constexpr int NSP = (20 - KR) / 2, NRP = KR / 2;
        uint32_t bf[2][4];
        lds128(bf[0], bb + NRP * 512);
        int rp = 0, cur = 0;
#pragma unroll
        for (int sp = 0; sp < NSP; sp++) {
          constexpr int dummy = 0; (void)dummy;
          const int nr = (sp == NSP - 1) ? 0 : (NRP + NSP - 2 - sp) / (NSP - 1);
          if (nr) lds128(bf[cur ^ 1], bb + rp * 512);
#pragma unroll
          for (int m = 0; m < 3; m++) mma16816(acc[m], Q[m], bf[cur][0], bf[cur][1]);
#pragma unroll
          for (int m = 0; m < 3; m++) mma16816(acc[m], Q[3 + m], bf[cur][2], bf[cur][3]);
          if (sp + 1 < NSP) {
#pragma unroll
            for (int n = 0; n < 6; n++) lds128(Q[n], swf + ((sp + 1) * 6 + n) * 512);
          }
          cur ^= 1;
#pragma unroll
          for (int q = 0; q < nr; q++) {
            if (q + 1 < nr) lds128(bf[cur ^ 1], bb + (rp + 1) * 512);
            else lds128(bf[cur ^ 1], bb + (NRP + sp + 1) * 512);
#pragma unroll
            for (int m = 0; m < 3; m++) mma16816(acc[m], wA[rp * 6 + m], bf[cur][0], bf[cur][1]);
#pragma unroll
            for (int m = 0; m < 3; m++) mma16816(acc[m], wA[rp * 6 + 3 + m], bf[cur][2], bf[cur][3]);
            rp++; cur ^= 1;
          }
        }
      }
      STAMP(2);
      const uint32_t red = l16 + OFF_RED + mg * 1536;
      if (kg == 0) sts128(red + 1024, __float_as_uint(acc[2][0]), __float_as_uint(acc[2][1]), __float_as_uint(acc[2][2]), __float_as_uint(acc[2][3]));
      else { sts128(red, __float_as_uint(acc[0][0]), __float_as_uint(acc[0][1]), __float_as_uint(acc[0][2]), __float_as_uint(acc[0][3]));
             sts128(red + 512, __float_as_uint(acc[1][0]), __float_as_uint(acc[1][1]), __float_as_uint(acc[1][2]), __float_as_uint(acc[1][3])); }
      bf16* const kvd = &g_KVm[0][0] + (lds32(cst + 516) + s * (NM * HD));
      if (kg == 0) {
        uint32_t ka = sbase + OFF_KX + b * 4608 + (((lane >> 4) & 1) * 8 + (lane & 7)) * 144 + (mg * 16 + ((lane >> 3) & 1) * 8) * 2;
        ldsm4(Q[0], ka); ldsm4(Q[1], ka + 16 * 144);
        bar_sync(3 + mg, 64);
        lds128(Q[2], red); lds128(Q[3], red + 512);
        uint32_t q0 = movm(pack_bf16(acc[0][0] + __uint_as_float(Q[2][0]), acc[0][1] + __uint_as_float(Q[2][1]))), q1 = movm(pack_bf16(acc[0][2] + __uint_as_float(Q[2][2]), acc[0][3] + __uint_as_float(Q[2][3])));
        uint32_t k0 = movm(pack_bf16(acc[1][0] + __uint_as_float(Q[3][0]), acc[1][1] + __uint_as_float(Q[3][1]))), k1 = movm(pack_bf16(acc[1][2] + __uint_as_float(Q[3][2]), acc[1][3] + __uint_as_float(Q[3][3])));
        float sp[5][4];
#pragma unroll
        for (int t = 0; t < 5; t++) sp[t][0] = sp[t][1] = sp[t][2] = sp[t][3] = 0.f;
        mma16816_4(sp[1], q0, 0, q1, 0, Q[0][0], Q[0][1]);
        mma16816_4(sp[2], q0, 0, q1, 0, Q[0][2], Q[0][3]);
        mma16816_4(sp[3], q0, 0, q1, 0, Q[1][0], Q[1][1]);
        mma16816_4(sp[4], q0, 0, q1, 0, Q[1][2], Q[1][3]);
        mma16816_4(sp[0], q0, 0, q1, 0, k0, k1);
        const uint32_t spb = l8 + OFF_SP + mg * 1280;
#pragma unroll
        for (int t = 0; t < 5; t++) sts64(spb + t * 256, __float_as_uint(sp[t][0]), __float_as_uint(sp[t][1]));
        *(uint32_t*)kvd = k0; *(uint32_t*)(kvd + 8) = k1;
      } else {
        bar_sync(3 + mg, 64);
        lds128(Q[2], red + 1024);
        uint32_t v0 = pack_bf16(acc[2][0] + __uint_as_float(Q[2][0]), acc[2][1] + __uint_as_float(Q[2][1])), v1 = pack_bf16(acc[2][2] + __uint_as_float(Q[2][2]), acc[2][3] + __uint_as_float(Q[2][3]));
        uint32_t dst = l8 + OFF_VM + (j * 4 + mg) * 256;
        if (s < NSEG - 1) st_async_v2(dst + peer_off, v0, v1, bar_x + peer_off);
        sts64(dst, v0, v1);
        uint32_t t0 = movm(v0), t1 = movm(v1);
        *(uint32_t*)kvd = t0; *(uint32_t*)(kvd + 8) = t1;
      }
      bar_sync(1, 256);
      if (s == NSEG - 1) { if (tid == 0) mbar_arrive(bar_empty + 8 * b); break; }
      if (warp < 5) {
        uint32_t x0[2], x1[2], x2[2], x3[2];
        const uint32_t spb = l8 + OFF_SP + warp * 256;
        lds64(x0, spb); lds64(x1, spb + 1280); lds64(x2, spb + 2560); lds64(x3, spb + 3840);
        float sx = (__uint_as_float(x0[0]) + __uint_as_float(x1[0])) + (__uint_as_float(x2[0]) + __uint_as_float(x3[0]));
        float sy = (__uint_as_float(x0[1]) + __uint_as_float(x1[1])) + (__uint_as_float(x2[1]) + __uint_as_float(x3[1]));
        uint32_t dst = l8 + OFF_SX + warp * 256 + j * 1280;
        st_async_v2(dst + peer_off, __float_as_uint(sx), __float_as_uint(sy), bar_x + peer_off);
        sts64(dst, __float_as_uint(sx), __float_as_uint(sy));
        __syncwarp();
        if (lane == 0) mbar_arrive(bar_x);
      }
      STAMP(3);
      uint32_t* const gp = &g_part[b][0][0][0];
      const uint32_t tag = ((s >> 1) + 1) & 3;
      uint32_t po[4];
      uint32_t t_5;
      auto wo_phase = [&](auto ntc, auto nqc, uint32_t (*R)[4]) {
        constexpr int NT = decltype(ntc)::value, NQ = decltype(nqc)::value;
        lds128(po, cst);
        bar_sync(1, 256);
        if (tid == 0) { mbar_arrive(bar_empty + 8 * b); if (s < NSEG - 2) mbar_expect_tx(bar_x, 2304); }
        STAMP(5);
        t_5 = clk32();
        uint32_t ob[4][4];
#pragma unroll
        for (int kp = 0; kp < 4; kp++) lds128(ob[kp], l16 + OFF_O + kp * 512);
#pragma unroll
        for (int i = 0; i < NT; i++) {
          float d[2][4];
#pragma unroll
          for (int q = 0; q < 2; q++) d[q][0] = d[q][1] = d[q][2] = d[q][3] = 0.f;
#pragma unroll
          for (int ks = 0; ks < 8; ks++) {
            uint32_t b0 = ob[ks >> 1][(ks & 1) * 2], b1 = ob[ks >> 1][(ks & 1) * 2 + 1];
            const int f = i * 8 + ks;
            if (f >= WF0 && f < WF0 + WR) mma16816(d[ks & 1], wO[f - WF0], b0, b1);
            else {
              const int n = f < WF0 ? f : f - WR;
              mma16816(d[ks & 1], R[n % NQ], b0, b1);
              if (n + NQ < NT * 8 - WR) lds128(R[n % NQ], swf + (NSQ + n + NQ) * 512);
            }
          }
          uint32_t w[4];
#pragma unroll
          for (int q = 0; q < 4; q++) w[q] = (__float_as_uint(d[0][q] + d[1][q]) & ~3u) | tag;
          st_relaxed_v4(gp + po[i], w[0], w[1], w[2], w[3]);
        }
      };
      if (warp >= 4) {
#pragma unroll
        for (int n = 0; n < 4; n++) lds128(Q[n], swf + (NSQ + n) * 512);
        uint32_t vx[4][4];
        {
          uint32_t va = sbase + OFF_VX + b * 8704 + (((lane >> 3) & 1) * 8 + (lane & 7)) * 272 + (mg * 32 + (lane >> 4) * 8) * 2;
          ldsm4t(vx[0], va); ldsm4t(vx[1], va + 16 * 272); ldsm4t(vx[2], va + 32); ldsm4t(vx[3], va + 16 * 272 + 32);
        }
        mbar_wait(bar_x, s & 1);
        STAMP(4);
        float p[10];
#pragma unroll
        for (int t = 0; t < 5; t++) { uint32_t u[4]; lds64(u, l8 + OFF_SX + t * 256); lds64(u + 2, l8 + OFF_SX + 1280 + t * 256);
          p[2 * t] = __uint_as_float(u[0]) + __uint_as_float(u[2]); p[2 * t + 1] = __uint_as_float(u[1]) + __uint_as_float(u[3]); }
        uint32_t vm[4]; lds64(vm, l8 + OFF_VM + mg * 512); lds64(vm + 2, l8 + OFF_VM + mg * 512 + 256);
        float mx = fmaxf(fmaxf(fmaxf(p[0], p[1]), fmaxf(p[2], p[3])), fmaxf(fmaxf(fmaxf(p[4], p[5]), fmaxf(p[6], p[7])), fmaxf(p[8], p[9])));
        mx = fmaxf(mx, __shfl_xor_sync(0xffffffffu, mx, 1)); mx = fmaxf(mx, __shfl_xor_sync(0xffffffffu, mx, 2));
        const float mxl = -mx * SL2E;
#pragma unroll
        for (int i = 2; i < 10; i++) p[i] = ex2(fmaf(p[i], SL2E, mxl));
        p[0] = ex2(fmaf(p[0], SL2E, mxl)); p[1] = ex2(fmaf(p[1], SL2E, mxl));
        uint32_t pa[5];
#pragma unroll
        for (int t = 0; t < 5; t++) pa[t] = pack_bf16(p[2 * t], p[2 * t + 1]);
        float o[4][4], o2[4][4];
#pragma unroll
        for (int q = 0; q < 4; q++) { o[q][0] = o[q][1] = o[q][2] = o[q][3] = 0.f; o2[q][0] = o2[q][1] = o2[q][2] = o2[q][3] = 0.f; }
#pragma unroll
        for (int q = 0; q < 4; q++) mma16816_4(o[q], pa[1], 0, pa[2], 0, vx[(q >> 1) * 2][(q & 1) * 2], vx[(q >> 1) * 2][(q & 1) * 2 + 1]);
#pragma unroll
        for (int q = 0; q < 4; q++) mma16816_4(o2[q], pa[3], 0, pa[4], 0, vx[(q >> 1) * 2 + 1][(q & 1) * 2], vx[(q >> 1) * 2 + 1][(q & 1) * 2 + 1]);
#pragma unroll
        for (int q = 0; q < 4; q++) mma1688(o[q], pa[0], 0, vm[q]);
        float sum = (((p[0] + p[1]) + (p[2] + p[3])) + ((p[4] + p[5]) + (p[6] + p[7]))) + (p[8] + p[9]);
        sum += __shfl_xor_sync(0xffffffffu, sum, 1); sum += __shfl_xor_sync(0xffffffffu, sum, 2);
        const float inv = rcp(sum);
        sts128(l16 + OFF_O + mg * 512, pack_bf16((o[0][0] + o2[0][0]) * inv, (o[0][1] + o2[0][1]) * inv), pack_bf16((o[1][0] + o2[1][0]) * inv, (o[1][1] + o2[1][1]) * inv),
                                       pack_bf16((o[2][0] + o2[2][0]) * inv, (o[2][1] + o2[2][1]) * inv), pack_bf16((o[3][0] + o2[3][0]) * inv, (o[3][1] + o2[3][1]) * inv));
        wo_phase(IC<2>{}, IC<4>{}, Q);
      } else {
        STAMP(4);
        uint32_t R[NQA][4];
#pragma unroll
        for (int n = 0; n < NQA; n++) lds128(R[n], swf + (NSQ + n) * 512);
        wo_phase(IC<3>{}, IC<NQA>{}, R);
      }
      STAMP(6);
      uint32_t cs[4]; lds128(cs, cst + 512);
      uint32_t* const gm = &g_memt[b ^ 1][0];
      if (warp >= 3) {
        const uint32_t* src = gp + po[3];
        while ((int)(clk32() - t_5) < (int)cs[2]) {}
        uint4 v[4];
        int adj = -ADJ_DN;
        while (true) {
#pragma unroll
          for (int k = 0; k < 4; k++) v[k] = ld_relaxed_v4(src + k * 8 * 80);
          uint32_t bad = 0;
#pragma unroll
          for (int k = 0; k < 4; k++) bad |= ((v[k].x ^ tag) | (v[k].y ^ tag)) | ((v[k].z ^ tag) | (v[k].w ^ tag));
          if (__all_sync(0xffffffffu, !(bad & 3))) break;
          adj = ADJ_UP;
          if (__any_sync(0xffffffffu, expired(sbase + B_BAR))) break;
        }
        float x = (__uint_as_float(v[0].x) + __uint_as_float(v[1].x)) + (__uint_as_float(v[2].x) + __uint_as_float(v[3].x));
        float y = (__uint_as_float(v[0].y) + __uint_as_float(v[1].y)) + (__uint_as_float(v[2].y) + __uint_as_float(v[3].y));
        float z = (__uint_as_float(v[0].z) + __uint_as_float(v[1].z)) + (__uint_as_float(v[2].z) + __uint_as_float(v[3].z));
        float w = (__uint_as_float(v[0].w) + __uint_as_float(v[1].w)) + (__uint_as_float(v[2].w) + __uint_as_float(v[3].w));
        const bool h4 = lane & 16, h3 = lane & 8;
        float e0 = (h4 ? z : x) + __shfl_xor_sync(0xffffffffu, h4 ? x : z, 16);
        float e1 = (h4 ? w : y) + __shfl_xor_sync(0xffffffffu, h4 ? y : w, 16);
        float f = (h3 ? e1 : e0) + __shfl_xor_sync(0xffffffffu, h3 ? e0 : e1, 8);
        f += __shfl_xor_sync(0xffffffffu, f, 4);
        if (!(lane & 4)) st_relaxed(gm + cs[0], pack_bf16(0.f, f) | (uint32_t)(s + 1));
        sts32(cst + 520, min(max((int)cs[2] + adj, 0), 8000));
      }
      STAMP(7);
      {
#pragma unroll
        for (int n = 0; n < 3; n++) lds128(Q[n], swf + n * 512);
        mbar_wait(bar_full + 8 * (b ^ 1), ((s + 1) >> 1) & 1);
        const uint32_t* src = gm + ((kg * 20 + mg) * 32 + lane) * 4;
        while ((int)(clk32() - t_5) < (int)cs[3]) {}
        uint4 v[5];
        const uint32_t sq = s + 1;
        int adj = -ADJ_DN;
        while (true) {
#pragma unroll
          for (int k = 0; k < 5; k++) v[k] = ld_relaxed_v4(src + 512 * k);
          uint32_t bad = 0;
#pragma unroll
          for (int k = 0; k < 5; k++) bad |= ((v[k].x ^ sq) | (v[k].y ^ sq)) | ((v[k].z ^ sq) | (v[k].w ^ sq));
          if (!(bad & 0xffff)) break;
          adj = ADJ_UP;
          if (expired(sbase + B_BAR)) break;
        }
        adj = __reduce_max_sync(0xffffffffu, adj);
        asm volatile("" : "+r"(tid_keep));
        const uint32_t mb_dst = sbase + ((((tid_keep >> 3) & 3) * 2 + (tid_keep & 1)) * 4 + ((tid_keep >> 1) & 3)) * 16 + OFF_MEMB + ((tid_keep >> 7) * 10 + ((tid_keep >> 6) & 1)) * 512 + ((tid_keep >> 5) & 1) * 8;
#pragma unroll
        for (int k = 0; k < 5; k++) sts64(mb_dst + k * 1024, __byte_perm(v[k].x, v[k].y, 0x7632), __byte_perm(v[k].z, v[k].w, 0x7632));
        lds128(Q[3], swf + 3 * 512);
#pragma unroll
        for (int n = 4; n < 6; n++) lds128(Q[n], swf + n * 512);
        sts32(cst + 524, min(max((int)cs[3] + adj, 0), 8000));
      }
      STAMP(0);
    }
}

#define TLS(i)
#define DEADLINE_NS 200000000
struct Ring { uint32_t st, ph; __device__ __forceinline__ void next() { if (++st == NST) { st = 0; ph ^= 1; } } };

__device__ __forceinline__ void flag_helper(const uint32_t sbase, int wg) {
  const uint32_t jb = sbase + B_BAR + BR_JOB + wg * 32;
  for (;;) {
    bar_sync(12 + wg, 160);
    const uint32_t fl = lds32(jb);
    __syncwarp();
    if ((threadIdx.x & 31) == 0) mbar_arrive(sbase + B_BAR + BR_SFREE + 8 * wg);
    if ((int)fl < 0) break;
    if ((threadIdx.x & 31) == 0) { __threadfence(); red_release((uint32_t*)&g_f + fl, 1); }
  }
}
struct Stg { uint32_t ph; };
__device__ __forceinline__ void post_flag(Stg& sg, const uint32_t sbase, uint32_t flag, int tid) {
  const int wg = tid >> 7;
  if ((tid & 127) == 0) { mbar_wait(sbase + B_BAR + BR_SFREE + 8 * wg, sg.ph); sts32(sbase + B_BAR + BR_JOB + wg * 32, flag); }
  sg.ph ^= 1;
  __syncwarp();
  bar_arrive(12 + wg, 160);
}
__device__ __forceinline__ void warp_store64(const float* acc, const uint32_t stg, bf16* dst  , int lane) {
  const int i = lane >> 3, rr = lane & 7;
#pragma unroll
  for (int jj = 0; jj < 8; jj += 2)
    stsm4(stg + ((i & 1) * 8 + rr) * 128 + (((jj + (i >> 1)) ^ rr) << 4), pack_bf16(acc[jj * 4 + 0], acc[jj * 4 + 1]), pack_bf16(acc[jj * 4 + 2], acc[jj * 4 + 3]),
          pack_bf16(acc[jj * 4 + 4], acc[jj * 4 + 5]), pack_bf16(acc[jj * 4 + 6], acc[jj * 4 + 7]));
  __syncwarp();
  uint32_t v[4][4];
#pragma unroll
  for (int q = 0; q < 4; q++) { const int r = q * 4 + i; lds128(v[q], stg + r * 128 + ((rr ^ (r & 7)) << 4)); }
#pragma unroll
  for (int q = 0; q < 4; q++) __stcg((uint4*)(dst + (size_t)(q * 4 + i) * HD + rr * 8), make_uint4(v[q][0], v[q][1], v[q][2], v[q][3]));
  __syncwarp();
}

__device__ __forceinline__ void kv_producer(const Params& p, const uint32_t sbase, int cb) {
  const uint32_t bb = sbase + B_BAR;
  const CUtensorMap* tw = cb < 32 ? &p.tmWk : &p.tmWv;
  const int n0 = (cb & 31) * 128;
  uint32_t st = 0, ph = 1;
#pragma unroll 1
  for (int it = 0; it < 160; it++) {
    const int rb = it / 10; int kb = it - rb * 10 + cb % 10; if (kb >= 10) kb -= 10;
    if (it < 10) {
      mbar_expect_tx(bb + BR_WF + 8 * kb, 16384);
      tma_load3(sbase + kb * 16384, tw, kb * 64, n0 >> 6, bb + BR_WF + 8 * kb);
    }
    mbar_wait<1>(bb + BR_XE + 8 * st, ph);
    const uint32_t fb = bb + BR_XF + 8 * st, sa = sbase + KV_X + st * 16384;
    mbar_expect_tx(fb, 16384);
    tma_load(sa, &p.tmX, kb * 64, rb * 128, fb);
    if (++st == 3) { st = 0; ph ^= 1; }
  }
}
__device__ __forceinline__ void kv_consumer(const Params& p, Stg& sg, const uint32_t sbase, int cb) {
  const int tid = opaque_tid(), wg = tid >> 7;
  const bool elect = (tid & 127) == 0;
  const uint32_t bb = sbase + B_BAR;
#pragma unroll 1
  for (int rb = wg; rb < 16; rb += 2) {
    float acc[128];
#pragma unroll
    for (int i = 0; i < 128; i++) acc[i] = 0.f;
    int it = rb * 10;
    uint32_t st = it % 3, ph = (it / 3) & 1;
    if (rb > 0) bar_sync(14 + wg, 256);
    uint32_t prev = 0;
#pragma unroll 1
    for (int ki = 0; ki < 10; ki++) {
      int kb = ki + cb % 10; if (kb >= 10) kb -= 10;
      if (rb < 2) mbar_wait(bb + BR_WF + 8 * kb, 0);
      mbar_wait(bb + BR_XF + 8 * st, ph);
      if (ki == 9 && rb < 15) bar_arrive(14 + (wg ^ 1), 256);
      const uint64_t da = make_desc(sbase + KV_X + st * 16384, 16, 1024);
      const uint64_t db = make_desc(sbase + kb * 16384, 8192, 1024);
      wg_fence();
#pragma unroll
      for (int k = 0; k < 4; k++) { wgmma_n128(acc, da + k * 2, db + k * 128); wgmma_n128(acc + 64, da + 512 + k * 2, db + k * 128); }
      wg_commit();
      if (ki > 0) { wg_wait<1>(); if (elect) mbar_arrive(bb + BR_XE + 8 * prev); }
      prev = st;
      if (++st == 3) { st = 0; ph ^= 1; }
    }
    wg_wait<0>();
    if (elect) mbar_arrive(bb + BR_XE + 8 * prev);
    const uint32_t stg = sbase + KV_STG + (tid >> 5) * 2048;
    bf16* dst = &g_KV[(cb >> 5) * SEQ + rb * 128 + ((tid >> 5) & 3) * 16][(cb & 31) * 128];
    warp_store64(acc, stg, dst, tid & 31);
    warp_store64(acc + 32, stg, dst + 64, tid & 31);
    warp_store64(acc + 64, stg, dst + 64 * HD, tid & 31);
    warp_store64(acc + 96, stg, dst + 64 * HD + 64, tid & 31);
    post_flag(sg, sbase, (uint32_t)(offsetof(Flags, kv) / 4) + rb * 64 + cb, tid);
  }
}

__device__ __forceinline__ void bulk_producer(const Params& p, const uint32_t sbase) {
  Ring r{0, 1};
  const uint32_t bb = sbase + B_BAR;
  for (int it = 0;; it++) {
    const int slot = it & 1;
    mbar_wait<1>(bb + BR_TQE + 8 * slot, ((it >> 1) & 1) ^ 1);
    int t = p.t_begin + (int)atomicAdd(&g_f.task_ctr, 1u);
    if (t >= p.t_end) t = N_TASKS;
    sts32(bb + BR_TASK + 4 * slot, t);
    mbar_arrive(bb + BR_TQF + 8 * slot);
    if (t >= N_TASKS) break;
    int rb, q, kcn; const int kind = decode(t, rb, q, kcn);
    if (kind < K_QA) {
      mbar_wait<1>(bb + BR_TQE + 8 * slot, (it >> 1) & 1);
    } else {
      if (kind == K_QA) {
#pragma unroll 1
        for (int kb = 0; kb < 10; kb++) {
          mbar_wait<1>(bb + BR_EMPTY + 8 * r.st, r.ph);
          const uint32_t fb = bb + BR_FULL + 8 * r.st, sa = sbase + r.st * STAGE;
          mbar_expect_tx(fb, 49152);
          tma_load(sa, &p.tmX, kb * 64, rb * 128, fb);
          tma_load3(sa + 16384, &p.tmWq, kb * 64, q * 4, fb);
          r.next();
        }
#pragma unroll 1
        for (int u = 0; u < 4; u++) {
          const int h = 2 * q + (u >> 1), kv = u & 1;
          wait_flag(sbase + B_BAR, &g_f.kv[rb][kv * 32 + h], 1);
          if (kv == 0) { wait_flag(sbase + B_BAR, &g_f.prog[2 * h][0], 4 * rb + 4); wait_flag(sbase + B_BAR, &g_f.prog[2 * h + 1][0], 4 * rb + 4); }
          fence_proxy_async();
          mbar_wait<1>(bb + BR_EMPTY + 8 * r.st, r.ph);
          const uint32_t fb = bb + BR_FULL + 8 * r.st, sa = sbase + r.st * STAGE;
          mbar_expect_tx(fb, 40960);
          tma_load3(sa, &p.tmKVl, kv * SEQ + rb * 128, h * 2, fb);
          tma_load3(sa + 32768, &p.tmKVm, kv * 512 + rb * 32, h * 2, fb);
          r.next();
        }
      } else {
        const int ct = q & 1, kc = q >> 1, nkb = 64 / kcn;
#pragma unroll 1
        for (int u = 0; u < 8 / kcn; u++) wait_flag(sbase + B_BAR, &g_f.o_rdy[rb][kc * (8 / kcn) + u], 8);
        fence_proxy_async();
#pragma unroll 1
        for (int kb = 0; kb < nkb; kb++) {
          mbar_wait<1>(bb + BR_EMPTY + 8 * r.st, r.ph);
          const uint32_t fb = bb + BR_FULL + 8 * r.st, sa = sbase + r.st * STAGE;
          mbar_expect_tx(fb, 57344);
          const int k0 = (kc * nkb + kb) * 64;
          tma_load(sa, &p.tmOl, k0, rb * 128, fb);
          tma_load3(sa + 16384, &p.tmWo, k0, ct * 5, fb);
          r.next();
        }
      }
    }
  }
}

template<int N>
__device__ __forceinline__ void gemm_mainloop(float* acc, Ring& r, const uint32_t sbase, int nkb, int wg, bool elect) {
  const uint32_t bb = sbase + B_BAR;
#pragma unroll
  for (int i = 0; i < N / 2; i++) acc[i] = 0.f;
#pragma unroll 1
  for (int kb = 0; kb < nkb; kb++) {
    mbar_wait(bb + BR_FULL + 8 * r.st, r.ph);
    const uint32_t sa = sbase + r.st * STAGE;
    const uint64_t da = make_desc(sa + wg * 8192, 16, 1024);
    const uint64_t db = make_desc(sa + 16384, 8192, 1024);
    wg_fence();
#pragma unroll
    for (int k = 0; k < 4; k++) {
      if (N == 256) wgmma_n256(acc, da + k * 2, db + k * 128);
      else { wgmma_n192(acc, da + k * 2, db + k * 128); wgmma_n128(acc + 96, da + k * 2, db + 1536 + k * 128); }
    }
    wg_commit();
    wg_wait<0>();
    if (elect) mbar_arrive(bb + BR_EMPTY + 8 * r.st);
    r.next();
  }
}

__device__ __forceinline__ uint32_t u2get(const uint2& v, int i) { return i == 0 ? v.x : v.y; }
constexpr int TP = 260;
__device__ __forceinline__ void task_prep(const Params& p, const uint32_t sbase, int rb) {
  const int tid = opaque_tid(), lane = tid & 31, warp = tid >> 5;
  const int r0 = rb * 128 + warp * 16;
#pragma unroll 1
  for (int k = 0; k < 5; k++) {
    const int d = (lane + 32 * k) * 4;
    uint2 kw[19], vw[16];
#pragma unroll
    for (int q = 0; q < 19; q++) kw[q] = (r0 - 3 + q >= 0) ? __ldg((const uint2*)(p.bk + (size_t)(r0 - 3 + q) * DM + d)) : make_uint2(0, 0);
#pragma unroll
    for (int q = 0; q < 16; q++) vw[q] = __ldg((const uint2*)(p.bv + (size_t)(r0 + q) * DM + d));
    const uint4 s0 = __ldg((const uint4*)(p.shift_k + d * 4)), s1 = __ldg((const uint4*)(p.shift_k + d * 4 + 8));
#pragma unroll
    for (int c = 0; c < 2; c++) {
      const uint4 s4 = c ? s1 : s0;
      const uint32_t tp[4] = {__byte_perm(s4.x, s4.z, 0x5410), __byte_perm(s4.x, s4.z, 0x7632), __byte_perm(s4.y, s4.w, 0x5410), __byte_perm(s4.y, s4.w, 0x7632)};
#pragma unroll
      for (int i0 = 0; i0 < 16; i0 += 2) {
        uint32_t kv[2];
#pragma unroll
        for (int i = 0; i < 2; i++) {
          uint32_t s = bmul2(u2get(kw[i0 + i], c), tp[3]);
#pragma unroll
          for (int q = 1; q < 4; q++) s = badd2(s, bmul2(u2get(kw[i0 + i + q], c), tp[3 - q]));
          kv[i] = bmul2(s, u2get(vw[i0 + i], c));
        }
        const uint32_t a = sbase + (d + 2 * c) * TP + (warp * 16 + i0) * 2;
        sts32(a, __byte_perm(kv[0], kv[1], 0x5410)); sts32(a + TP, __byte_perm(kv[0], kv[1], 0x7632));
      }
    }
  }
  {
    uint2 gw[5];
#pragma unroll
    for (int k = 0; k < 5; k++) gw[k] = __ldg((const uint2*)(p.gate_w + (lane + 32 * k) * 4));
#pragma unroll 1
    for (int i0 = 0; i0 < 16; i0 += 8) {
      uint2 xv[8][5];
#pragma unroll
      for (int i = 0; i < 8; i++)
#pragma unroll
        for (int k = 0; k < 5; k++) xv[i][k] = __ldg((const uint2*)(p.x + (size_t)(r0 + i0 + i) * DM + (lane + 32 * k) * 4));
      float s[8];
#pragma unroll
      for (int i = 0; i < 8; i++) {
        s[i] = 0.f;
#pragma unroll
        for (int k = 0; k < 5; k++) {
          const uint32_t m0 = bmul2(xv[i][k].x, gw[k].x), m1 = bmul2(xv[i][k].y, gw[k].y);
          s[i] += (bflo(m0) + bfhi(m0)) + (bflo(m1) + bfhi(m1));
        }
      }
#pragma unroll
      for (int i = 0; i < 4; i++) { const bool hi = lane & 4; const float a = hi ? s[i + 4] : s[i], b = hi ? s[i] : s[i + 4]; s[i] = a + __shfl_xor_sync(0xffffffffu, b, 4); }
#pragma unroll
      for (int i = 0; i < 2; i++) { const bool hi = lane & 2; const float a = hi ? s[i + 2] : s[i], b = hi ? s[i] : s[i + 2]; s[i] = a + __shfl_xor_sync(0xffffffffu, b, 2); }
      { const bool hi = lane & 1; const float a = hi ? s[1] : s[0], b = hi ? s[0] : s[1]; s[0] = a + __shfl_xor_sync(0xffffffffu, b, 1); }
      s[0] += __shfl_xor_sync(0xffffffffu, s[0], 8); s[0] += __shfl_xor_sync(0xffffffffu, s[0], 16);
      if (lane < 8) g_gate[r0 + i0 + lane] = bf16r(rcp(1.0f + ex2(-1.4426950408889634f * bf16r(s[0]))));
    }
  }
  bar_sync(1, 256);
#pragma unroll 4
  for (int d = warp; d < DM; d += 8) {
    const uint32_t a = sbase + d * TP + lane * 8;
    *(uint2*)(&g_kvT[d][rb * 128 + lane * 4]) = make_uint2(lds32(a), lds32(a + 4));
  }
  fence_proxy_async_smem();
  bar_sync(1, 256);
  if (tid == 0) { __threadfence(); red_release(&g_f.prep, 1); }
}
__device__ __forceinline__ void task_post(const Params& p, const uint32_t sbase, int rb) {
  const int tid = opaque_tid(), lane = tid & 31, warp = tid >> 5;
  if (tid == 0) wait_flag(sbase + B_BAR, &g_f.conv, 80 * 8);
  bar_sync(1, 256);
#pragma unroll 1
  for (int d0 = warp; d0 < DM; d0 += 320) {
    uint2 v[40];
#pragma unroll
    for (int q = 0; q < 40; q++) v[q] = __ldcg((const uint2*)(&g_ybT[d0 + q * 8][rb * 128 + lane * 4]));
#pragma unroll
    for (int q = 0; q < 40; q++) { const uint32_t a = sbase + (d0 + q * 8) * TP + lane * 8; sts32(a, v[q].x); sts32(a + 4, v[q].y); }
  }
  bar_sync(1, 256);
#pragma unroll 1
  for (int it = 0; it < 5; it++) {
    const int d = (lane + 32 * it) * 4, rl = warp * 16;
    uint2 xv[16];
#pragma unroll
    for (int i = 0; i < 16; i++) xv[i] = __ldg((const uint2*)(p.x + (size_t)(rb * 128 + rl + i) * DM + d));
#pragma unroll
    for (int i = 0; i < 16; i += 2) {
      const uint2 x0 = xv[i], x1 = xv[i + 1];
      const uint32_t a = sbase + d * TP + (rl + i) * 2;
      const uint32_t y0 = lds32(a), y1 = lds32(a + TP), y2 = lds32(a + 2 * TP), y3 = lds32(a + 3 * TP);
      *(uint2*)(&g_B[rb * 128 + rl + i][d]) = make_uint2(bmul2(x0.x, __byte_perm(y0, y1, 0x5410)), bmul2(x0.y, __byte_perm(y2, y3, 0x5410)));
      *(uint2*)(&g_B[rb * 128 + rl + i + 1][d]) = make_uint2(bmul2(x1.x, __byte_perm(y0, y1, 0x7632)), bmul2(x1.y, __byte_perm(y2, y3, 0x7632)));
    }
  }
  fence_proxy_async_smem();
  bar_sync(1, 256);
  if (tid == 0) { __threadfence(); red_release(&g_f.post[rb], 1); }
}

constexpr int CV_U = 0, CV_UCH = 5120;
constexpr int CV_W = 8 * CV_UCH, CV_WCH = 9216;
__device__ __forceinline__ void conv_mma(float (&acc)[4][4][4], uint32_t (&e)[15], const uint32_t ub, const uint32_t wb, int lane) {
#pragma unroll 1
  for (int m = 0; m < 32; m++) {
#pragma unroll
    for (int i = 0; i < 7; i++) e[i] = e[i + 8];
#pragma unroll
    for (int i = 7; i < 15; i++) e[i] = lds32(wb + (8 * m + i - 7) * 32);
    const int jr = 8 + (lane & 7) - m;
    const uint32_t ba = ub + jr * 128 + (((lane >> 3) ^ (jr & 7)) << 4);
#pragma unroll
    for (int nt = 3; nt >= 0; nt--) {
      if (nt < (m >> 3)) break;
      uint32_t b0[4], b1[4];
      ldsm4(b0, ba + nt * 1024); ldsm4(b1, (ba ^ 64) + nt * 1024);
#pragma unroll
      for (int ks = 0; ks < 4; ks++) {
        const uint32_t x0 = ks < 2 ? b0[(ks & 1) * 2] : b1[(ks & 1) * 2], x1 = ks < 2 ? b0[(ks & 1) * 2 + 1] : b1[(ks & 1) * 2 + 1];
#pragma unroll
        for (int mt = 0; mt < 4; mt++) {
          const int c = 2 * (mt - ks) + 7;
          mma16816_4(acc[mt][nt], e[c], e[c + 1], e[c - 1], e[c], x0, x1);
        }
      }
    }
  }
}

__device__ __forceinline__ void task_conv(const Params& p, uint32_t& cvph, const uint32_t sbase, int ci) {
  const int tid = opaque_tid(), lane = tid & 31, warp = tid >> 5;
  const int d = ci * 8 + warp;
  const uint32_t ub = sbase + CV_U + warp * CV_UCH, wb0 = sbase + CV_W + warp * CV_WCH;
  const uint32_t bar = sbase + B_BAR + BR_CV;
  TLS(3600 + ci * 5);
  if (tid == 0) {
    wait_flag(sbase + B_BAR, &g_f.prep, 16);
    fence_proxy_async();
    mbar_expect_tx(bar, 8 * 4096);
#pragma unroll 1
    for (int c = 0; c < 8; c++) tma_load(sbase + CV_U + c * CV_UCH + 1024, &p.tmKT, 0, (ci * 8 + c) * 32, bar);
  }
  sts128(ub + lane * 16, 0, 0, 0, 0); sts128(ub + 512 + lane * 16, 0, 0, 0, 0);
  if (lane < 16) sts128(wb0 + lane * 16, 0, 0, 0, 0);
  {
    const bf16* kf = p.ssm_k + (size_t)d * SEQ;
#pragma unroll 1
    for (int q0 = 0; q0 < 8; q0 += 4) {
      uint4 fv[4]; uint32_t fp[4];
#pragma unroll
      for (int q = 0; q < 4; q++) { const int i = lane + 32 * (q0 + q); fv[q] = __ldg((const uint4*)(kf + i * 8)); fp[q] = i ? (uint32_t)__ldg((const unsigned short*)(kf + i * 8 - 1)) : 0u; }
#pragma unroll
      for (int q = 0; q < 4; q++) {
        const uint4 v = fv[q];
        const uint32_t a = wb0 + (64 + (lane + 32 * (q0 + q)) * 8) * 4;
        sts128(a, (v.x & 0xffff) | (fp[q] << 16), __byte_perm(v.x, v.x, 0x1032), __byte_perm(v.y, v.x, 0x7610), __byte_perm(v.y, v.y, 0x1032));
        sts128(a + 16, __byte_perm(v.z, v.y, 0x7610), __byte_perm(v.z, v.z, 0x1032), __byte_perm(v.w, v.z, 0x7610), __byte_perm(v.w, v.w, 0x1032));
      }
    }
  }
  __syncwarp();
  mbar_wait(bar, cvph); cvph ^= 1;
  TLS(3600 + ci * 5 + 1);
  {
    const int g = lane >> 2, c4 = lane & 3;
    float acc[4][4][4];
#pragma unroll
    for (int a = 0; a < 4; a++)
#pragma unroll
      for (int b = 0; b < 4; b++) acc[a][b][0] = acc[a][b][1] = acc[a][b][2] = acc[a][b][3] = 0.f;
    const uint32_t wb = wb0 + (64 + g - 2 * c4) * 4;
    uint32_t e[15];
#pragma unroll
    for (int i = 8; i < 15; i++) e[i] = lds32(wb + (i - 15) * 32);
    conv_mma(acc, e, ub, wb, lane);
    __syncwarp();
    TLS(3600 + ci * 5 + 2);
#pragma unroll
    for (int nt = 0; nt < 4; nt++)
#pragma unroll
      for (int mp = 0; mp < 2; mp++)
        stsm4t(wb0 + (nt * 8 + (lane & 7)) * 128 + (((mp * 4 + (lane >> 3)) ^ (lane & 7)) << 4), pack_bf16(acc[2 * mp][nt][0], acc[2 * mp][nt][1]), pack_bf16(acc[2 * mp][nt][2], acc[2 * mp][nt][3]),
               pack_bf16(acc[2 * mp + 1][nt][0], acc[2 * mp + 1][nt][1]), pack_bf16(acc[2 * mp + 1][nt][2], acc[2 * mp + 1][nt][3]));
  }
  __syncwarp();
  TLS(3600 + ci * 5 + 3);
  {
    const uint32_t dd = (uint32_t)__ldg((const unsigned short*)(p.ssm_D + d)) * 0x10001u;
#pragma unroll 1
    for (int q = 0; q < 8; q++) {
      uint32_t k4[4], y4[4];
      const uint32_t o = (lane + 32 * q) * 16;
      lds128(k4, ub + 1024 + o); lds128(y4, wb0 + o);
#pragma unroll
      for (int i = 0; i < 4; i++) y4[i] = badd2(y4[i], bmul2(k4[i], dd));
      sts128(wb0 + o, y4[0], y4[1], y4[2], y4[3]);
    }
  }
  fence_proxy_async_smem();
  __syncwarp();
  if (lane == 0) {
    tma_store(&p.tmYT, wb0, 0, d * 32);
    tma_commit(); tma_wait0(); fence_proxy_async(); __threadfence(); red_release(&g_f.conv, 1);
  }
  TLS(3600 + ci * 5 + 4);
  bar_sync(1, 256);
}

__device__ __forceinline__ void task_qa(const Params& p, Ring& r, Stg& sg, const uint32_t sbase, int rb, int hp) {
  const int tid = opaque_tid(), lane = tid & 31, wg = tid >> 7, warp = tid >> 5;
  const bool elect = (tid & 127) == 0;
  const uint32_t bb = sbase + B_BAR;
  const int g = lane >> 2, c4 = lane & 3;
  uint32_t qa[16][4];
  {
    float acc[128];
    gemm_mainloop<256>(acc, r, sbase, 10, wg, elect);
#pragma unroll
    for (int ks = 0; ks < 16; ks++) {
      qa[ks][0] = pack_bf16(acc[ks * 8 + 0], acc[ks * 8 + 1]); qa[ks][1] = pack_bf16(acc[ks * 8 + 2], acc[ks * 8 + 3]);
      qa[ks][2] = pack_bf16(acc[ks * 8 + 4], acc[ks * 8 + 5]); qa[ks][3] = pack_bf16(acc[ks * 8 + 6], acc[ks * 8 + 7]);
    }
  }
  const int seg = warp >> 1, half = warp & 1;
  const int rr = lane & 7, i = lane >> 3;
#pragma unroll 1
  for (int hh = 0; hh < 2; hh++) {
    float sc[5][4];
#pragma unroll
    for (int t = 0; t < 5; t++) sc[t][0] = sc[t][1] = sc[t][2] = sc[t][3] = 0.f;
    {
      mbar_wait(bb + BR_FULL + 8 * r.st, r.ph);
      const uint32_t sa = sbase + r.st * STAGE;
#pragma unroll
      for (int ks = 0; ks < 8; ks++) {
        const int eh = ks >> 2, chunk = (ks & 3) * 2 + (i & 1);
        uint32_t kx[4];
        ldsm4(kx, sa + eh * 16384 + (seg * 32 + (i >> 1) * 8 + rr) * 128 + ((chunk ^ rr) << 4));
        mma16816(sc[1], qa[ks], kx[0], kx[1]);
        mma16816(sc[2], qa[ks], kx[2], kx[3]);
        if (half) {
          ldsm4(kx, sa + eh * 16384 + (seg * 32 + 16 + (i >> 1) * 8 + rr) * 128 + ((chunk ^ rr) << 4));
          mma16816(sc[3], qa[ks], kx[0], kx[1]);
          mma16816(sc[4], qa[ks], kx[2], kx[3]);
        }
        if ((ks & 1) == 0) {
          const int ch2 = (ks & 3) * 2 + i;
          ldsm4(kx, sa + 32768 + eh * 4096 + (seg * 8 + rr) * 128 + ((ch2 ^ rr) << 4));
          mma16816(sc[0], qa[ks], kx[0], kx[1]);
          mma16816(sc[0], qa[ks + 1], kx[2], kx[3]);
        }
      }
      bar_sync(7 + wg, 128);
      if (elect) mbar_arrive(bb + BR_EMPTY + 8 * r.st);
      r.next();
    }
#pragma unroll
    for (int ks = 0; ks < 8; ks++) { qa[ks][0] = qa[ks + 8][0]; qa[ks][1] = qa[ks + 8][1]; qa[ks][2] = qa[ks + 8][2]; qa[ks][3] = qa[ks + 8][3]; }
    uint32_t pa[5][2];
    {
      const float scale = 0.08838834764831845f, L2E = 1.4426950408889634f;
#pragma unroll
      for (int rh = 0; rh < 2; rh++) {
        const int row = half * 16 + rh * 8 + g;
        float v[10];
#pragma unroll
        for (int t = 0; t < 5; t++) {
          uint32_t pk = pack_bf16(sc[t][rh * 2], sc[t][rh * 2 + 1]);
          pk = pack_bf16(bflo(pk) * scale, bfhi(pk) * scale);
          v[2 * t] = bflo(pk); v[2 * t + 1] = bfhi(pk);
          if (t > 0) { const int key = (t - 1) * 8 + 2 * c4; if (key > row) v[2 * t] = -1e9f; if (key + 1 > row) v[2 * t + 1] = -1e9f; }
        }
        float mx = v[0];
#pragma unroll
        for (int q = 1; q < 10; q++) mx = fmaxf(mx, v[q]);
        mx = fmaxf(mx, __shfl_xor_sync(0xffffffffu, mx, 1)); mx = fmaxf(mx, __shfl_xor_sync(0xffffffffu, mx, 2));
        float sum = 0.f;
#pragma unroll
        for (int q = 0; q < 10; q++) { v[q] = ex2((v[q] - mx) * L2E); sum += v[q]; }
        sum += __shfl_xor_sync(0xffffffffu, sum, 1); sum += __shfl_xor_sync(0xffffffffu, sum, 2);
        const float inv = rcp(sum);
#pragma unroll
        for (int t = 0; t < 5; t++) pa[t][rh] = pack_bf16(v[2 * t] * inv, v[2 * t + 1] * inv);
      }
    }
    float acc[64];
#pragma unroll
    for (int q = 0; q < 64; q++) acc[q] = 0.f;
    {
      mbar_wait(bb + BR_FULL + 8 * r.st, r.ph);
      const uint32_t sa = sbase + r.st * STAGE;
#pragma unroll
      for (int np = 0; np < 8; np++) {
        const int eh = np >> 2, chunk = (np & 3) * 2 + (i >> 1);
        uint32_t vx[4];
        ldsm4t(vx, sa + eh * 16384 + (seg * 32 + (i & 1) * 8 + rr) * 128 + ((chunk ^ rr) << 4));
        mma16816_4(acc + np * 8, pa[1][0], pa[1][1], pa[2][0], pa[2][1], vx[0], vx[1]);
        mma16816_4(acc + np * 8 + 4, pa[1][0], pa[1][1], pa[2][0], pa[2][1], vx[2], vx[3]);
        if (half) {
          ldsm4t(vx, sa + eh * 16384 + (seg * 32 + 16 + (i & 1) * 8 + rr) * 128 + ((chunk ^ rr) << 4));
          mma16816_4(acc + np * 8, pa[3][0], pa[3][1], pa[4][0], pa[4][1], vx[0], vx[1]);
          mma16816_4(acc + np * 8 + 4, pa[3][0], pa[3][1], pa[4][0], pa[4][1], vx[2], vx[3]);
        }
        if ((np & 1) == 0) {
          const int ch2 = (np & 3) * 2 + i;
          ldsm4t(vx, sa + 32768 + eh * 4096 + (seg * 8 + rr) * 128 + ((ch2 ^ rr) << 4));
          mma1688(acc + np * 8, pa[0][0], pa[0][1], vx[0]);
          mma1688(acc + np * 8 + 4, pa[0][0], pa[0][1], vx[1]);
          mma1688(acc + np * 8 + 8, pa[0][0], pa[0][1], vx[2]);
          mma1688(acc + np * 8 + 12, pa[0][0], pa[0][1], vx[3]);
        }
      }
      bar_sync(7 + wg, 128);
      if (elect) mbar_arrive(bb + BR_EMPTY + 8 * r.st);
      r.next();
    }
    const int h = 2 * hp + hh;
    bf16* dst = &g_O[rb * 128 + warp * 16][h * 128];
    warp_store64(acc, sbase + B_STG + warp * 2048, dst, lane);
    warp_store64(acc + 32, sbase + B_STG + warp * 2048, dst + 64, lane);
    post_flag(sg, sbase, (uint32_t)(offsetof(Flags, o_rdy) / 4) + rb * 8 + (h >> 2), tid);
  }
}

__device__ __forceinline__ uint32_t mix2(float a0, float a1, uint32_t bv, uint32_t gt, uint32_t og) {
  return badd2(bmul2(gt, pack_bf16(a0, a1)), bmul2(og, bv));
}
__device__ __forceinline__ void task_op(const Params& p, Ring& r, const uint32_t sbase, int rb, int ct, int kc, int kcn) {
  const int tid = opaque_tid();
  {
    const int lane = tid & 31, wg = tid >> 7, wq = (tid >> 5) & 3;
    float acc[160];
    gemm_mainloop<320>(acc, r, sbase, 64 / kcn, wg, (tid & 127) == 0);
    float* dst = &g_P[kc][rb * 128 + wg * 64 + wq * 16 + (lane >> 2)][ct * 320 + 2 * (lane & 3)];
#pragma unroll
    for (int j = 0; j < 40; j++) {
      __stcg((float2*)(dst + j * 8), make_float2(acc[j * 4], acc[j * 4 + 1]));
      __stcg((float2*)(dst + 8 * DM + j * 8), make_float2(acc[j * 4 + 2], acc[j * 4 + 3]));
    }
  }
  bar_sync(1, 256);
  if (tid == 0) {
    __threadfence();
    const uint32_t tk = atomicAdd(&g_f.op_wr[rb][ct], 1u);
    const bool fin = kcn == 8 || tk == 1;
    if (fin) { wait_flag(sbase + B_BAR, &g_f.op_wr[rb][ct], kcn); wait_flag(sbase + B_BAR, &g_f.post[rb], 1); }
    sts32(sbase + B_BAR + BR_MISC, fin);
  }
  bar_sync(1, 256);
  if (lds32(sbase + B_BAR + BR_MISC)) {
    const int row0 = rb * 128 + (kcn == 8 ? kc * 16 : 0), nit = kcn == 8 ? 5 : 40;
#pragma unroll 1
    for (int u = 0; u < nit; u += 5) {
      float4 s[5]; uint2 bv[5]; float gt[5]; int o[5];
#pragma unroll
      for (int i = 0; i < 5; i++) {
        const int idx = (u + i) * 256 + tid, row = row0 + idx / 80;
        o[i] = row * DM + ct * 320 + (idx % 80) * 4;
        s[i] = __ldcg((const float4*)(&g_P[0][0][0] + o[i]));
        bv[i] = __ldcg((const uint2*)(&g_B[0][0] + o[i]));
        gt[i] = __ldcg(&g_gate[row]);
      }
#pragma unroll 1
      for (int q = 1; q < kcn; q++) {
        float4 w[5];
#pragma unroll
        for (int i = 0; i < 5; i++) w[i] = __ldcg((const float4*)(&g_P[q][0][0] + o[i]));
#pragma unroll
        for (int i = 0; i < 5; i++) { s[i].x += w[i].x; s[i].y += w[i].y; s[i].z += w[i].z; s[i].w += w[i].w; }
      }
#pragma unroll
      for (int i = 0; i < 5; i++) {
        const uint32_t g2 = pack_bf16(gt[i], gt[i]), og = pack_bf16(1.0f - gt[i], 1.0f - gt[i]);
        *(uint2*)(p.out + o[i]) = make_uint2(mix2(s[i].x, s[i].y, bv[i].x, g2, og), mix2(s[i].z, s[i].w, bv[i].y, g2, og));
      }
    }
  }
}

__device__ __forceinline__ void bulk_consumer(const Params& p, Stg& sg, const uint32_t sbase) {
  Ring r{0, 0};
  uint32_t cvph = 0;
  const uint32_t bb = sbase + B_BAR;
  for (int it = 0;; it++) {
    const int slot = it & 1;
    mbar_wait(bb + BR_TQF + 8 * slot, (it >> 1) & 1);
    const int t = (int)lds32(bb + BR_TASK + 4 * slot);
    if (t >= N_TASKS) break;
    int rb, q, kcn; const int kind = decode(t, rb, q, kcn);
    if (kind == K_PREP) task_prep(p, sbase, rb);
    else if (kind == K_CONV) task_conv(p, cvph, sbase, q);
    else if (kind == K_POST) task_post(p, sbase, rb);
    else if (kind == K_QA) task_qa(p, r, sg, sbase, rb, q);
    else task_op(p, r, sbase, rb, q & 1, q >> 1, kcn);
    bar_sync(7 + (threadIdx.x >> 7), 128);
    if ((threadIdx.x & 127) == 0) mbar_arrive(bb + BR_TQE + 8 * slot);
  }
}

__global__ void __cluster_dims__(2, 1, 1) __launch_bounds__(384, 1) mega_kernel(const __grid_constant__ Params p) {
  extern __shared__ __align__(1024) unsigned char sm[];
  const int tid = threadIdx.x, warp = tid >> 5;
  const uint32_t sbase = smem_u32(sm);
  const uint32_t bb = sbase + B_BAR;
  const bool is_chain = p.do_chain && blockIdx.x < 64;
  const int kvb = (int)blockIdx.x - (p.do_chain ? 64 : 0);
  const bool is_kv = p.do_kv && !is_chain && kvb < 64;
  if (tid == 0) {
    for (int i = 0; i < NST; i++) { mbar_init(bb + BR_FULL + 8 * i, 1); mbar_init(bb + BR_EMPTY + 8 * i, 2); mbar_init(bb + BR_XF + 8 * i, 1); mbar_init(bb + BR_XE + 8 * i, 1); }
    for (int i = 0; i < 2; i++) { mbar_init(bb + BR_TQF + 8 * i, 1); mbar_init(bb + BR_TQE + 8 * i, 2); mbar_init(bb + BR_KVF + 8 * i, 32); mbar_init(bb + BR_KVE + 8 * i, 1); mbar_init(bb + BR_SFREE + 8 * i, 1); }
    for (int i = 0; i < 10; i++) mbar_init(bb + BR_WF + 8 * i, 1);
    mbar_init(bb + BR_X, 6); mbar_init(bb + BR_CV, 1);
    { uint32_t t; asm volatile("mov.u32 %0, %%globaltimer_lo;" : "=r"(t)); sts32(bb + 1016, t + DEADLINE_NS); }
    asm volatile("fence.mbarrier_init.release.cluster;" ::: "memory");
  }
  __syncthreads();
  cluster_sync_all();
  if (warp >= 8) {
    if (is_chain) {
      asm volatile("setmaxnreg.dec.sync.aligned.u32 24;");
      if (warp == 8) chain_producer(sbase);
      bar_sync(11, 384);
      asm volatile("setmaxnreg.inc.sync.aligned.u32 40;");
    } else {
      asm volatile("setmaxnreg.dec.sync.aligned.u32 40;");
    }
    if (warp == 8) {
      if (is_kv) { if (tid == 256) kv_producer(p, sbase, kvb); __syncwarp(); bar_sync(2, 288); }
      if (tid == 256) bulk_producer(p, sbase);
      __syncwarp();
    } else if (warp < 11) flag_helper(sbase, warp - 9);
  } else {
    if (is_chain) {
      asm volatile("setmaxnreg.inc.sync.aligned.u32 240;");
      chain_consumer(p, sm, sbase);
      fence_proxy_async_smem();
      asm volatile("setmaxnreg.dec.sync.aligned.u32 232;");
      bar_sync(11, 384);
    } else {
      asm volatile("setmaxnreg.inc.sync.aligned.u32 232;");
    }
    Stg sg{1};
    if (is_kv) {
      kv_consumer(p, sg, sbase, kvb);
      fence_proxy_async_smem();
      bar_sync(2, 288);
    }
    bulk_consumer(p, sg, sbase);
    post_flag(sg, sbase, 0xffffffffu, tid);
  }
  __syncthreads();
  if (tid == 0 && expired(bb)) g_err = 1;
  if (p.do_reset) {
    if (tid == 0) { __threadfence(); sts32(bb + BR_MISC, atomicAdd(&g_f.exit_ctr, 1u)); }
    __syncthreads();
    if (lds32(bb + BR_MISC) == gridDim.x - 1) {
#pragma unroll 1
      for (int i = tid; i < (int)(sizeof(Flags) / 4); i += 384) ((uint32_t*)&g_f)[i] = 0;
#pragma unroll 1
      for (int i = tid; i < 2560; i += 384) g_mem[3][i] = 0;
    }
  }
}

typedef CUresult (*EncFn)(CUtensorMap*, CUtensorMapDataType, cuuint32_t, void*, const cuuint64_t*, const cuuint64_t*, const cuuint32_t*, const cuuint32_t*,
                          CUtensorMapInterleave, CUtensorMapSwizzle, CUtensorMapL2promotion, CUtensorMapFloatOOBfill);
static void make_map(EncFn enc, CUtensorMap* m, const void* base, uint64_t inner, uint64_t outer, uint32_t box_in, uint32_t box_out) {
  cuuint64_t dims[2] = {inner, outer}; cuuint64_t strides[1] = {inner * 2};
  cuuint32_t box[2] = {box_in, box_out}; cuuint32_t es[2] = {1, 1};
  enc(m, CU_TENSOR_MAP_DATA_TYPE_BFLOAT16, 2, (void*)base, dims, strides, box, es, CU_TENSOR_MAP_INTERLEAVE_NONE, CU_TENSOR_MAP_SWIZZLE_128B,
      CU_TENSOR_MAP_L2_PROMOTION_L2_256B, CU_TENSOR_MAP_FLOAT_OOB_FILL_NONE);
}
static void make_map3(EncFn enc, CUtensorMap* m, const void* base, uint64_t inner, uint64_t outer, uint32_t box_rows, uint32_t box_slabs) {
  cuuint64_t dims[3] = {64, outer, inner / 64}; cuuint64_t strides[2] = {inner * 2, 128};
  cuuint32_t box[3] = {64, box_rows, box_slabs}; cuuint32_t es[3] = {1, 1, 1};
  enc(m, CU_TENSOR_MAP_DATA_TYPE_BFLOAT16, 3, (void*)base, dims, strides, box, es, CU_TENSOR_MAP_INTERLEAVE_NONE, CU_TENSOR_MAP_SWIZZLE_128B,
      CU_TENSOR_MAP_L2_PROMOTION_L2_256B, CU_TENSOR_MAP_FLOAT_OOB_FILL_NONE);
}
static void fill_params(Params& p, void* const* d_in, void* d_out) {
  static EncFn enc = nullptr;
  if (!enc) {
    void* fn = nullptr; cudaDriverEntryPointQueryResult qr;
    cudaGetDriverEntryPoint("cuTensorMapEncodeTiled", &fn, cudaEnableDefault, &qr);
    enc = (EncFn)fn;
    cudaFuncSetAttribute(mega_kernel, cudaFuncAttributeMaxDynamicSharedMemorySize, SMEM_TOTAL);
  }
  void *kv, *kvm, *o, *kt, *yt;
  cudaGetSymbolAddress(&kt, g_kvT); cudaGetSymbolAddress(&yt, g_ybT);
  cudaGetSymbolAddress(&kv, g_KV); cudaGetSymbolAddress(&kvm, g_KVm); cudaGetSymbolAddress(&o, g_O);
  p.x = (const bf16*)d_in[0]; p.mem0 = (const bf16*)d_in[1]; p.Wq = (const bf16*)d_in[2]; p.Wk = (const bf16*)d_in[3];
  p.Wv = (const bf16*)d_in[4]; p.Wo = (const bf16*)d_in[5];
  p.bk = (const bf16*)d_in[8]; p.bv = (const bf16*)d_in[9]; p.shift_k = (const bf16*)d_in[10]; p.ssm_k = (const bf16*)d_in[11];
  p.ssm_D = (const bf16*)d_in[12]; p.gate_w = (const bf16*)d_in[13];
  p.out = (bf16*)d_out;
  make_map(enc, &p.tmX, p.x, DM, SEQ, 64, 128);
  make_map(enc, &p.tmO, o, HD, SEQ, 64, 64);
  make_map(enc, &p.tmOl, o, HD, SEQ, 64, 128);
  make_map(enc, &p.tmKV, kv, HD, 2 * SEQ, 64, 64);
  make_map3(enc, &p.tmKVl, kv, HD, 2 * SEQ, 128, 2);
  make_map3(enc, &p.tmKVm, kvm, HD, 2 * NSEG * NM, 32, 2);
  make_map3(enc, &p.tmWq, p.Wq, HD, DM, 64, 4);
  make_map3(enc, &p.tmWk, p.Wk, HD, DM, 64, 2);
  make_map3(enc, &p.tmWv, p.Wv, HD, DM, 64, 2);
  make_map3(enc, &p.tmWo, p.Wo, DM, HD, 64, 5);
  make_map(enc, &p.tmW1[0], p.Wq, HD, DM, 64, 64);
  make_map(enc, &p.tmW1[1], p.Wk, HD, DM, 64, 64);
  make_map(enc, &p.tmW1[2], p.Wv, HD, DM, 64, 64);
  make_map(enc, &p.tmWo1, p.Wo, DM, HD, 64, 128);
  make_map(enc, &p.tmKT, kt, 64, DM * 32, 64, 32);
  make_map(enc, &p.tmYT, yt, 64, DM * 32, 64, 32);
  p.dG = 1200; p.dG2 = 2600;
  p.t_begin = 0; p.t_end = N_TASKS; p.do_chain = 1; p.do_reset = 1; p.do_kv = 1;
}

extern "C" void kernel_launch(void* const* d_in, const int* in_sizes, int n_in, void* d_out, int out_size) {
  Params p;
  fill_params(p, d_in, d_out);
  mega_kernel<<<132, 384, SMEM_TOTAL>>>(p);
}
```

```cpp
#include <cuda_runtime.h>
#include <cuda_bf16.h>
#include <cuda.h>
#include <stdint.h>
#include <stddef.h>

typedef __nv_bfloat16 bf16;
constexpr int SEQ = 2048, DM = 640, DH = 128, NM = 8, SEG = 32, NSEG = 64, HD = 4096;

__device__ __forceinline__ uint32_t smem_u32(const void* p) { return (uint32_t)__cvta_generic_to_shared(p); }
__device__ __forceinline__ uint32_t mapa(uint32_t a, uint32_t r) { uint32_t d; asm volatile("mapa.shared::cluster.u32 %0, %1, %2;" : "=r"(d) : "r"(a), "r"(r)); return d; }
__device__ __forceinline__ void mbar_init(uint32_t a, uint32_t c) { asm volatile("mbarrier.init.shared::cta.b64 [%0], %1;" :: "r"(a), "r"(c) : "memory"); }
__device__ __forceinline__ void mbar_expect_tx(uint32_t a, uint32_t tx) { asm volatile("mbarrier.arrive.expect_tx.shared::cta.b64 _, [%0], %1;" :: "r"(a), "r"(tx) : "memory"); }
__device__ __forceinline__ void mbar_arrive(uint32_t a) { asm volatile("mbarrier.arrive.shared::cta.b64 _, [%0];" :: "r"(a) : "memory"); }
__device__ __forceinline__ bool mbar_try(uint32_t a, uint32_t ph) {
  uint32_t ok; asm volatile("{ .reg .pred p; mbarrier.try_wait.parity.shared::cta.b64 p, [%1], %2; selp.u32 %0, 1, 0, p; }" : "=r"(ok) : "r"(a), "r"(ph) : "memory"); return ok; }
__device__ int g_err;
__device__ __forceinline__ bool expired(uint32_t blk) {
  uint32_t t, d; asm volatile("mov.u32 %0, %%globaltimer_lo;" : "=r"(t)); asm volatile("ld.shared.u32 %0, [%1+1016];" : "=r"(d) : "r"(blk));
  return (int)(t - d) > 0; }
__device__ __forceinline__ int opaque_tid() { int t; asm volatile("mov.u32 %0, %%tid.x;" : "=r"(t)); return t; }
template<int ROLE = 0> __device__ __forceinline__ void mbar_wait(uint32_t a, uint32_t ph) {
  asm volatile("{\n .reg .pred p;\n .reg .u32 t, d;\n"
    "W: mbarrier.try_wait.parity.shared::cta.b64 p, [%0], %1;\n @p bra D;\n"
    " mov.u32 t, %%globaltimer_lo;\n and.b32 d, %0, 0xFFFFFC00;\n ld.shared.u32 d, [d+1016];\n sub.u32 t, t, d;\n setp.le.s32 p, t, 0;\n @p bra W;\n"
    "D:\n }" :: "r"(a), "r"(ph) : "memory"); }
__device__ __forceinline__ void st_async_v2(uint32_t addr, uint32_t x, uint32_t y, uint32_t mbar) {
  asm volatile("st.async.weak.shared::cluster.mbarrier::complete_tx::bytes.v2.b32 [%0], {%1,%2}, [%3];" :: "r"(addr), "r"(x), "r"(y), "r"(mbar) : "memory"); }
__device__ __forceinline__ void cluster_sync_all() { asm volatile("barrier.cluster.arrive.release.aligned; barrier.cluster.wait.acquire.aligned;" ::: "memory"); }
__device__ __forceinline__ void bar_sync(int id, int n) { asm volatile("bar.sync %0, %1;" :: "r"(id), "r"(n) : "memory"); }
__device__ __forceinline__ void bar_arrive(int id, int n) { asm volatile("bar.arrive %0, %1;" :: "r"(id), "r"(n) : "memory"); }
__device__ __forceinline__ uint4 ld_relaxed_v4(const uint32_t* p) { uint4 v; asm volatile("ld.relaxed.gpu.global.v4.u32 {%0,%1,%2,%3}, [%4];" : "=r"(v.x), "=r"(v.y), "=r"(v.z), "=r"(v.w) : "l"(p) : "memory"); return v; }
__device__ __forceinline__ void st_relaxed_v4(uint32_t* p, uint32_t a, uint32_t b, uint32_t c, uint32_t d) { asm volatile("st.relaxed.gpu.global.v4.u32 [%0], {%1,%2,%3,%4};" :: "l"(p), "r"(a), "r"(b), "r"(c), "r"(d) : "memory"); }
__device__ __forceinline__ void st_relaxed(uint32_t* p, uint32_t v) { asm volatile("st.relaxed.gpu.global.u32 [%0], %1;" :: "l"(p), "r"(v) : "memory"); }
__device__ __forceinline__ uint32_t ld_acquire(const uint32_t* p) { uint32_t v; asm volatile("ld.acquire.gpu.global.u32 %0, [%1];" : "=r"(v) : "l"(p) : "memory"); return v; }
__device__ __forceinline__ void red_release(uint32_t* p, uint32_t v) { asm volatile("red.release.gpu.global.add.u32 [%0], %1;" :: "l"(p), "r"(v) : "memory"); }
__device__ __forceinline__ void st_release(uint32_t* p, uint32_t v) { asm volatile("st.release.gpu.global.u32 [%0], %1;" :: "l"(p), "r"(v) : "memory"); }
__device__ __forceinline__ void wait_flag(uint32_t blk, const uint32_t* p, uint32_t target) {
  while (ld_acquire(p) < target) { __nanosleep(64); if (expired(blk)) break; } }
__device__ __forceinline__ void fence_proxy_async() { asm volatile("fence.proxy.async;" ::: "memory"); }
__device__ __forceinline__ void fence_proxy_async_smem() { asm volatile("fence.proxy.async.shared::cta;" ::: "memory"); }
__device__ __forceinline__ void mma16816(float* d, const uint32_t* a, uint32_t b0, uint32_t b1) {
  asm volatile("mma.sync.aligned.m16n8k16.row.col.f32.bf16.bf16.f32 {%0,%1,%2,%3}, {%4,%5,%6,%7}, {%8,%9}, {%0,%1,%2,%3};"
    : "+f"(d[0]), "+f"(d[1]), "+f"(d[2]), "+f"(d[3]) : "r"(a[0]), "r"(a[1]), "r"(a[2]), "r"(a[3]), "r"(b0), "r"(b1)); }
__device__ __forceinline__ void mma16816_4(float* d, uint32_t a0, uint32_t a1, uint32_t a2, uint32_t a3, uint32_t b0, uint32_t b1) {
  asm volatile("mma.sync.aligned.m16n8k16.row.col.f32.bf16.bf16.f32 {%0,%1,%2,%3}, {%4,%5,%6,%7}, {%8,%9}, {%0,%1,%2,%3};"
    : "+f"(d[0]), "+f"(d[1]), "+f"(d[2]), "+f"(d[3]) : "r"(a0), "r"(a1), "r"(a2), "r"(a3), "r"(b0), "r"(b1)); }
__device__ __forceinline__ void mma1688(float* d, uint32_t a0, uint32_t a1, uint32_t b0) {
  asm volatile("mma.sync.aligned.m16n8k8.row.col.f32.bf16.bf16.f32 {%0,%1,%2,%3}, {%4,%5}, {%6}, {%0,%1,%2,%3};"
    : "+f"(d[0]), "+f"(d[1]), "+f"(d[2]), "+f"(d[3]) : "r"(a0), "r"(a1), "r"(b0)); }
__device__ __forceinline__ void ldsm4(uint32_t* r, uint32_t addr) { asm volatile("ldmatrix.sync.aligned.m8n8.x4.shared.b16 {%0,%1,%2,%3}, [%4];" : "=r"(r[0]), "=r"(r[1]), "=r"(r[2]), "=r"(r[3]) : "r"(addr) : "memory"); }
__device__ __forceinline__ void ldsm4t(uint32_t* r, uint32_t addr) { asm volatile("ldmatrix.sync.aligned.m8n8.x4.trans.shared.b16 {%0,%1,%2,%3}, [%4];" : "=r"(r[0]), "=r"(r[1]), "=r"(r[2]), "=r"(r[3]) : "r"(addr) : "memory"); }
__device__ __forceinline__ void stsm4(uint32_t addr, uint32_t a, uint32_t b, uint32_t c, uint32_t d) { asm volatile("stmatrix.sync.aligned.m8n8.x4.shared.b16 [%0], {%1,%2,%3,%4};" :: "r"(addr), "r"(a), "r"(b), "r"(c), "r"(d) : "memory"); }
__device__ __forceinline__ void stsm4t(uint32_t addr, uint32_t a, uint32_t b, uint32_t c, uint32_t d) { asm volatile("stmatrix.sync.aligned.m8n8.x4.trans.shared.b16 [%0], {%1,%2,%3,%4};" :: "r"(addr), "r"(a), "r"(b), "r"(c), "r"(d) : "memory"); }
__device__ __forceinline__ uint32_t movm(uint32_t a) { uint32_t d; asm volatile("movmatrix.sync.aligned.m8n8.trans.b16 %0, %1;" : "=r"(d) : "r"(a)); return d; }
__device__ __forceinline__ uint32_t pack_bf16(float lo, float hi) { uint32_t d; asm("cvt.rn.bf16x2.f32 %0, %1, %2;" : "=r"(d) : "f"(hi), "f"(lo)); return d; }
__device__ __forceinline__ uint32_t bmul2(uint32_t a, uint32_t b) { uint32_t d; asm("mul.rn.bf16x2 %0, %1, %2;" : "=r"(d) : "r"(a), "r"(b)); return d; }
__device__ __forceinline__ uint32_t badd2(uint32_t a, uint32_t b) { uint32_t d; asm("add.rn.bf16x2 %0, %1, %2;" : "=r"(d) : "r"(a), "r"(b)); return d; }
__device__ __forceinline__ float bf16r(float x) { return __uint_as_float(pack_bf16(0.f, x)); }
__device__ __forceinline__ float bflo(uint32_t v) { return __uint_as_float(v << 16); }
__device__ __forceinline__ float bfhi(uint32_t v) { return __uint_as_float(v & 0xffff0000u); }
__device__ __forceinline__ uint32_t clk32() { uint32_t c; asm volatile("mov.u32 %0, %%clock;" : "=r"(c)); return c; }
__device__ __forceinline__ void lds128(uint32_t* r, uint32_t a) { asm volatile("ld.shared.v4.b32 {%0,%1,%2,%3}, [%4];" : "=r"(r[0]), "=r"(r[1]), "=r"(r[2]), "=r"(r[3]) : "r"(a) : "memory"); }
__device__ __forceinline__ void lds64(uint32_t* r, uint32_t a) { asm volatile("ld.shared.v2.b32 {%0,%1}, [%2];" : "=r"(r[0]), "=r"(r[1]) : "r"(a) : "memory"); }
__device__ __forceinline__ uint32_t lds32(uint32_t a) { uint32_t r; asm volatile("ld.shared.b32 %0, [%1];" : "=r"(r) : "r"(a) : "memory"); return r; }
__device__ __forceinline__ uint32_t lds16(uint32_t a) { uint16_t r; asm volatile("ld.shared.u16 %0, [%1];" : "=h"(r) : "r"(a) : "memory"); return r; }
__device__ __forceinline__ void sts128(uint32_t a, uint32_t x, uint32_t y, uint32_t z, uint32_t w) { asm volatile("st.shared.v4.b32 [%0], {%1,%2,%3,%4};" :: "r"(a), "r"(x), "r"(y), "r"(z), "r"(w) : "memory"); }
__device__ __forceinline__ void sts64(uint32_t a, uint32_t x, uint32_t y) { asm volatile("st.shared.v2.b32 [%0], {%1,%2};" :: "r"(a), "r"(x), "r"(y) : "memory"); }
__device__ __forceinline__ void sts32(uint32_t a, uint32_t x) { asm volatile("st.shared.b32 [%0], %1;" :: "r"(a), "r"(x) : "memory"); }
__device__ __forceinline__ void sts16(uint32_t a, uint32_t x) { asm volatile("st.shared.u16 [%0], %1;" :: "r"(a), "h"((uint16_t)x) : "memory"); }
__device__ __forceinline__ float ex2(float x) { float y; asm("ex2.approx.ftz.f32 %0, %1;" : "=f"(y) : "f"(x)); return y; }
__device__ __forceinline__ float rcp(float x) { float y; asm("rcp.approx.ftz.f32 %0, %1;" : "=f"(y) : "f"(x)); return y; }
__device__ __forceinline__ void tma_load(uint32_t dst, const CUtensorMap* tm, int c0, int c1, uint32_t bar) {
  asm volatile("cp.async.bulk.tensor.2d.shared::cluster.global.mbarrier::complete_tx::bytes [%0], [%1, {%3, %4}], [%2];"
    :: "r"(dst), "l"((uint64_t)tm), "r"(bar), "r"(c0), "r"(c1) : "memory"); }
__device__ __forceinline__ void tma_load3(uint32_t dst, const CUtensorMap* tm, int c1, int c2, uint32_t bar) {
  asm volatile("cp.async.bulk.tensor.3d.shared::cluster.global.mbarrier::complete_tx::bytes [%0], [%1, {%3, %4, %5}], [%2];"
    :: "r"(dst), "l"((uint64_t)tm), "r"(bar), "r"(0), "r"(c1), "r"(c2) : "memory"); }
__device__ __forceinline__ void tma_store(const CUtensorMap* tm, uint32_t src, int c0, int c1) {
  asm volatile("cp.async.bulk.tensor.2d.global.shared::cta.bulk_group [%0, {%2, %3}], [%1];" :: "l"((uint64_t)tm), "r"(src), "r"(c0), "r"(c1) : "memory"); }
__device__ __forceinline__ void tma_commit() { asm volatile("cp.async.bulk.commit_group;" ::: "memory"); }
__device__ __forceinline__ void tma_wait_read0() { asm volatile("cp.async.bulk.wait_group.read 0;" ::: "memory"); }
__device__ __forceinline__ void tma_wait0() { asm volatile("cp.async.bulk.wait_group 0;" ::: "memory"); }
__device__ __forceinline__ void wg_fence() { asm volatile("wgmma.fence.sync.aligned;" ::: "memory"); }
__device__ __forceinline__ void wg_commit() { asm volatile("wgmma.commit_group.sync.aligned;" ::: "memory"); }
template<int N> __device__ __forceinline__ void wg_wait() { asm volatile("wgmma.wait_group.sync.aligned %0;" :: "n"(N) : "memory"); }
__device__ __forceinline__ uint64_t make_desc(uint32_t addr, uint32_t lbo, uint32_t sbo) {
  return (uint64_t)((addr & 0x3FFFF) >> 4) | ((uint64_t)(lbo >> 4) << 16) | ((uint64_t)(sbo >> 4) << 32) | (1ull << 62); }
__device__ __forceinline__ void wgmma_n128(float* d, uint64_t da, uint64_t db) {
  asm volatile("wgmma.mma_async.sync.aligned.m64n128k16.f32.bf16.bf16 {%0, %1, %2, %3, %4, %5, %6, %7, %8, %9, %10, %11, %12, %13, %14, %15, %16, %17, %18, %19, %20, %21, %22, %23, %24, %25, %26, %27, %28, %29, %30, %31, %32, %33, %34, %35, %36, %37, %38, %39, %40, %41, %42, %43, %44, %45, %46, %47, %48, %49, %50, %51, %52, %53, %54, %55, %56, %57, %58, %59, %60, %61, %62, %63}, %64, %65, 1, 1, 1, 0, 1;"
    : "+f"(d[0]), "+f"(d[1]), "+f"(d[2]), "+f"(d[3]), "+f"(d[4]), "+f"(d[5]), "+f"(d[6]), "+f"(d[7]), "+f"(d[8]), "+f"(d[9]), "+f"(d[10]), "+f"(d[11]), "+f"(d[12]), "+f"(d[13]), "+f"(d[14]), "+f"(d[15]), "+f"(d[16]), "+f"(d[17]), "+f"(d[18]), "+f"(d[19]), "+f"(d[20]), "+f"(d[21]), "+f"(d[22]), "+f"(d[23]), "+f"(d[24]), "+f"(d[25]), "+f"(d[26]), "+f"(d[27]), "+f"(d[28]), "+f"(d[29]), "+f"(d[30]), "+f"(d[31]), "+f"(d[32]), "+f"(d[33]), "+f"(d[34]), "+f"(d[35]), "+f"(d[36]), "+f"(d[37]), "+f"(d[38]), "+f"(d[39]), "+f"(d[40]), "+f"(d[41]), "+f"(d[42]), "+f"(d[43]), "+f"(d[44]), "+f"(d[45]), "+f"(d[46]), "+f"(d[47]), "+f"(d[48]), "+f"(d[49]), "+f"(d[50]), "+f"(d[51]), "+f"(d[52]), "+f"(d[53]), "+f"(d[54]), "+f"(d[55]), "+f"(d[56]), "+f"(d[57]), "+f"(d[58]), "+f"(d[59]), "+f"(d[60]), "+f"(d[61]), "+f"(d[62]), "+f"(d[63])
    : "l"(da), "l"(db));
}

__device__ __forceinline__ void wgmma_n192(float* d, uint64_t da, uint64_t db) {
  asm volatile("wgmma.mma_async.sync.aligned.m64n192k16.f32.bf16.bf16 {%0, %1, %2, %3, %4, %5, %6, %7, %8, %9, %10, %11, %12, %13, %14, %15, %16, %17, %18, %19, %20, %21, %22, %23, %24, %25, %26, %27, %28, %29, %30, %31, %32, %33, %34, %35, %36, %37, %38, %39, %40, %41, %42, %43, %44, %45, %46, %47, %48, %49, %50, %51, %52, %53, %54, %55, %56, %57, %58, %59, %60, %61, %62, %63, %64, %65, %66, %67, %68, %69, %70, %71, %72, %73, %74, %75, %76, %77, %78, %79, %80, %81, %82, %83, %84, %85, %86, %87, %88, %89, %90, %91, %92, %93, %94, %95}, %96, %97, 1, 1, 1, 0, 1;"
    : "+f"(d[0]), "+f"(d[1]), "+f"(d[2]), "+f"(d[3]), "+f"(d[4]), "+f"(d[5]), "+f"(d[6]), "+f"(d[7]), "+f"(d[8]), "+f"(d[9]), "+f"(d[10]), "+f"(d[11]), "+f"(d[12]), "+f"(d[13]), "+f"(d[14]), "+f"(d[15]), "+f"(d[16]), "+f"(d[17]), "+f"(d[18]), "+f"(d[19]), "+f"(d[20]), "+f"(d[21]), "+f"(d[22]), "+f"(d[23]), "+f"(d[24]), "+f"(d[25]), "+f"(d[26]), "+f"(d[27]), "+f"(d[28]), "+f"(d[29]), "+f"(d[30]), "+f"(d[31]), "+f"(d[32]), "+f"(d[33]), "+f"(d[34]), "+f"(d[35]), "+f"(d[36]), "+f"(d[37]), "+f"(d[38]), "+f"(d[39]), "+f"(d[40]), "+f"(d[41]), "+f"(d[42]), "+f"(d[43]), "+f"(d[44]), "+f"(d[45]), "+f"(d[46]), "+f"(d[47]), "+f"(d[48]), "+f"(d[49]), "+f"(d[50]), "+f"(d[51]), "+f"(d[52]), "+f"(d[53]), "+f"(d[54]), "+f"(d[55]), "+f"(d[56]), "+f"(d[57]), "+f"(d[58]), "+f"(d[59]), "+f"(d[60]), "+f"(d[61]), "+f"(d[62]), "+f"(d[63]), "+f"(d[64]), "+f"(d[65]), "+f"(d[66]), "+f"(d[67]), "+f"(d[68]), "+f"(d[69]), "+f"(d[70]), "+f"(d[71]), "+f"(d[72]), "+f"(d[73]), "+f"(d[74]), "+f"(d[75]), "+f"(d[76]), "+f"(d[77]), "+f"(d[78]), "+f"(d[79]), "+f"(d[80]), "+f"(d[81]), "+f"(d[82]), "+f"(d[83]), "+f"(d[84]), "+f"(d[85]), "+f"(d[86]), "+f"(d[87]), "+f"(d[88]), "+f"(d[89]), "+f"(d[90]), "+f"(d[91]), "+f"(d[92]), "+f"(d[93]), "+f"(d[94]), "+f"(d[95])
    : "l"(da), "l"(db));
}

__device__ __forceinline__ void wgmma_n256(float* d, uint64_t da, uint64_t db) {
  asm volatile("wgmma.mma_async.sync.aligned.m64n256k16.f32.bf16.bf16 {%0, %1, %2, %3, %4, %5, %6, %7, %8, %9, %10, %11, %12, %13, %14, %15, %16, %17, %18, %19, %20, %21, %22, %23, %24, %25, %26, %27, %28, %29, %30, %31, %32, %33, %34, %35, %36, %37, %38, %39, %40, %41, %42, %43, %44, %45, %46, %47, %48, %49, %50, %51, %52, %53, %54, %55, %56, %57, %58, %59, %60, %61, %62, %63, %64, %65, %66, %67, %68, %69, %70, %71, %72, %73, %74, %75, %76, %77, %78, %79, %80, %81, %82, %83, %84, %85, %86, %87, %88, %89, %90, %91, %92, %93, %94, %95, %96, %97, %98, %99, %100, %101, %102, %103, %104, %105, %106, %107, %108, %109, %110, %111, %112, %113, %114, %115, %116, %117, %118, %119, %120, %121, %122, %123, %124, %125, %126, %127}, %128, %129, 1, 1, 1, 0, 1;"
    : "+f"(d[0]), "+f"(d[1]), "+f"(d[2]), "+f"(d[3]), "+f"(d[4]), "+f"(d[5]), "+f"(d[6]), "+f"(d[7]), "+f"(d[8]), "+f"(d[9]), "+f"(d[10]), "+f"(d[11]), "+f"(d[12]), "+f"(d[13]), "+f"(d[14]), "+f"(d[15]), "+f"(d[16]), "+f"(d[17]), "+f"(d[18]), "+f"(d[19]), "+f"(d[20]), "+f"(d[21]), "+f"(d[22]), "+f"(d[23]), "+f"(d[24]), "+f"(d[25]), "+f"(d[26]), "+f"(d[27]), "+f"(d[28]), "+f"(d[29]), "+f"(d[30]), "+f"(d[31]), "+f"(d[32]), "+f"(d[33]), "+f"(d[34]), "+f"(d[35]), "+f"(d[36]), "+f"(d[37]), "+f"(d[38]), "+f"(d[39]), "+f"(d[40]), "+f"(d[41]), "+f"(d[42]), "+f"(d[43]), "+f"(d[44]), "+f"(d[45]), "+f"(d[46]), "+f"(d[47]), "+f"(d[48]), "+f"(d[49]), "+f"(d[50]), "+f"(d[51]), "+f"(d[52]), "+f"(d[53]), "+f"(d[54]), "+f"(d[55]), "+f"(d[56]), "+f"(d[57]), "+f"(d[58]), "+f"(d[59]), "+f"(d[60]), "+f"(d[61]), "+f"(d[62]), "+f"(d[63]), "+f"(d[64]), "+f"(d[65]), "+f"(d[66]), "+f"(d[67]), "+f"(d[68]), "+f"(d[69]), "+f"(d[70]), "+f"(d[71]), "+f"(d[72]), "+f"(d[73]), "+f"(d[74]), "+f"(d[75]), "+f"(d[76]), "+f"(d[77]), "+f"(d[78]), "+f"(d[79]), "+f"(d[80]), "+f"(d[81]), "+f"(d[82]), "+f"(d[83]), "+f"(d[84]), "+f"(d[85]), "+f"(d[86]), "+f"(d[87]), "+f"(d[88]), "+f"(d[89]), "+f"(d[90]), "+f"(d[91]), "+f"(d[92]), "+f"(d[93]), "+f"(d[94]), "+f"(d[95]), "+f"(d[96]), "+f"(d[97]), "+f"(d[98]), "+f"(d[99]), "+f"(d[100]), "+f"(d[101]), "+f"(d[102]), "+f"(d[103]), "+f"(d[104]), "+f"(d[105]), "+f"(d[106]), "+f"(d[107]), "+f"(d[108]), "+f"(d[109]), "+f"(d[110]), "+f"(d[111]), "+f"(d[112]), "+f"(d[113]), "+f"(d[114]), "+f"(d[115]), "+f"(d[116]), "+f"(d[117]), "+f"(d[118]), "+f"(d[119]), "+f"(d[120]), "+f"(d[121]), "+f"(d[122]), "+f"(d[123]), "+f"(d[124]), "+f"(d[125]), "+f"(d[126]), "+f"(d[127])
    : "l"(da), "l"(db));
}

__device__ __align__(1024) bf16 g_KV[2 * SEQ][HD];
__device__ __align__(1024) bf16 g_KVm[2 * NSEG * NM][HD];
__device__ __align__(1024) bf16 g_O[SEQ][HD];
__device__ __align__(1024) float g_P[8][SEQ][DM];
__device__ __align__(1024) float g_PF[2][16][128][DM];
__device__ __align__(1024) bf16 g_B[SEQ][DM];
__device__ __align__(1024) bf16 g_kvT[DM][SEQ];
__device__ __align__(1024) bf16 g_ybT[DM][SEQ];
__device__ float g_gate[SEQ];
__device__ __align__(128) uint32_t g_part[2][64][32][80];
__device__ __align__(128) uint32_t g_memt[2][5120];
struct Flags {
  uint32_t task_ctr, exit_ctr, prep, conv, pad0[28];
  uint32_t kv[16][64];
  uint32_t prog[64][8];
  uint32_t o_rdy[16][16];
  uint32_t op_wr[16][8];
  uint32_t post[16];
};
__device__ __align__(128) Flags g_f;

struct Params {
  CUtensorMap tmX, tmO, tmKV, tmKVm, tmWq, tmWk, tmWv, tmWo, tmKT, tmYT, tmOl, tmKVl, tmW1[3], tmWo1, tmWo2;
  const bf16 *x, *mem0, *Wq, *Wk, *Wv, *Wo, *bk, *bv, *shift_k, *ssm_k, *ssm_D, *gate_w;
  bf16* out;
  int dG, dG2;
  int t_begin, t_end, do_chain, do_reset, do_kv;
};

#define FINE_KC 16
constexpr int T_CONV = 16, T_QA0 = 96, T_POST = 128, T_G = 144, T_TAIL = T_G + 12 * 20, T_FINE = T_TAIL + 64, FKC = FINE_KC, N_TASKS = T_FINE + 10 * FKC;
enum { K_PREP, K_CONV, K_POST, K_QA, K_OP };
__device__ __forceinline__ int decode(int t, int& rb, int& q, int& kcn) {
  kcn = 2; q = 0;
  if (t < T_CONV) { rb = t; return K_PREP; }
  if (t < T_QA0) { rb = 0; q = t - T_CONV; return K_CONV; }
  if (t < T_POST) { rb = (t - T_QA0) >> 4; q = t & 15; return K_QA; }
  if (t < T_G) { rb = t - T_POST; return K_POST; }
  if (t < T_TAIL) { const int g = (t - T_G) / 20; q = (t - T_G) - g * 20; if (q < 4) { rb = g; return K_OP; } q -= 4; rb = g + 2; return K_QA; }
  if (t < T_FINE) { const int u = (t - T_TAIL) >> 4; q = (t - T_TAIL) & 15; kcn = 8; if (u & 1) { rb = 14 + (u >> 1); return K_QA; } rb = 12 + (u >> 1); return K_OP; }
  kcn = 16; q = t - T_FINE; rb = 14; if (q >= 5 * FKC) { q -= 5 * FKC; rb = 15; } return K_OP;
}

constexpr int STAGE = 57344, NST = 3;
constexpr int B_STG = 196608;
constexpr int B_BAR = B_STG + 32768;
constexpr int SMEM_TOTAL = B_BAR + 1024;
constexpr int KV_X = 163840, KV_STG = KV_X + 3 * 16384;
constexpr int BR_FULL = 0, BR_EMPTY = 32, BR_TQF = 64, BR_TQE = 80, BR_TASK = 96, BR_X = 128, BR_KVF = 136, BR_KVE = 152, BR_MISC = 168,
              BR_SFREE = 176, BR_JOB = 192  , BR_WF = 256  , BR_XF = 336, BR_XE = 360, BR_CV = 384;

#define KR 12
#define WR 6
#define ADJ_DN 4
#define ADJ_UP 48
#define PRO_DELAY 0
#define NQP 9
#define NACC 6
constexpr int WF0 = 4;
#define NQA 9
template<int V> struct IC { static constexpr int value = V; };
constexpr int NSQ = (20 - KR) * 3;
constexpr int NSF_LO = NSQ + 24 - WR, NSF_HI = NSQ + 16 - WR;
constexpr int OFF_WF = 0;
constexpr int OFF_RT = OFF_WF + 4 * (NSF_LO + NSF_HI) * 512;
constexpr int OFF_MEMB = OFF_RT;
constexpr int OFF_RED = OFF_MEMB + 10240;
constexpr int OFF_SP = OFF_RED + 6144;
constexpr int OFF_SX = OFF_SP + 5120;
constexpr int OFF_VM = OFF_SX + 2560;
constexpr int OFF_O = OFF_VM + 2048;
constexpr int OFF_KX = OFF_O + 2048;
constexpr int OFF_VX = OFF_KX + 9216;
constexpr int OFF_CST = OFF_VX + 17408;
constexpr int OFF_RT_END = OFF_CST + 8192;
static_assert(WF0 + WR <= 16 && OFF_RT <= B_BAR && OFF_RT_END + 4096 <= B_BAR, "chain smem");
#define STAMP(i)

#define PST(i)
__device__ __forceinline__ void chain_prefetch(const uint32_t sbase, int s, int h, int j, int lane) {
  const int b = s & 1;
  if ((s & 3) == 0) {
    if (lane == 0) { wait_flag(sbase + B_BAR, &g_f.kv[s >> 2][h], 1); wait_flag(sbase + B_BAR, &g_f.kv[s >> 2][32 + h], 1); }
    __syncwarp();
  }
  const bf16* kp = &g_KV[s * SEG][h * DH + j * 64];
  const bf16* vp = &g_KV[SEQ + s * SEG][h * DH];
#pragma unroll 2
  for (int k = 0; k < 8; k++) { int c = lane + 32 * k;
    asm volatile("cp.async.cg.shared.global [%0], [%1], 16;" :: "r"(sbase + OFF_KX + b * 4608 + (c >> 3) * 144 + (c & 7) * 16), "l"(kp + (size_t)(c >> 3) * HD + (c & 7) * 8) : "memory"); }
#pragma unroll 2
  for (int k = 0; k < 16; k++) { int c = lane + 32 * k;
    asm volatile("cp.async.cg.shared.global [%0], [%1], 16;" :: "r"(sbase + OFF_VX + b * 8704 + (c >> 4) * 272 + (c & 15) * 16), "l"(vp + (size_t)(c >> 4) * HD + (c & 15) * 8) : "memory"); }
  asm volatile("cp.async.mbarrier.arrive.noinc.shared::cta.b64 [%0];" :: "r"(sbase + B_BAR + BR_KVF + 8 * b) : "memory");
}

__device__ __forceinline__ void chain_producer(const uint32_t sbase) {
  const int lane = threadIdx.x & 31;
  const int h = blockIdx.x >> 1, j = blockIdx.x & 1;
  bar_sync(2, 288);
  chain_prefetch(sbase, 0, h, j, lane);
  chain_prefetch(sbase, 1, h, j, lane);
  for (int s = 0; s < NSEG; s++) {
    mbar_wait<1>(sbase + B_BAR + BR_KVE + 8 * (s & 1), (s >> 1) & 1);
    if (s + 2 < NSEG) chain_prefetch(sbase, s + 2, h, j, lane);
    if ((s & 3) == 3) {
      if (s + 1 < NSEG) __nanosleep(600);
      if (lane == 0) { __threadfence(); st_release(&g_f.prog[blockIdx.x][0], s + 1); }
      __syncwarp();
    }
  }
}

__device__ __forceinline__ void chain_consumer(const Params& a, unsigned char* sm, const uint32_t sbase) {
    const int tid = opaque_tid(), lane = tid & 31, warp = tid >> 5;
    const int h = blockIdx.x >> 1, j = blockIdx.x & 1;
    const uint32_t bar_x = sbase + B_BAR + BR_X, bar_full = sbase + B_BAR + BR_KVF, bar_empty = sbase + B_BAR + BR_KVE;
    const int kg = warp >> 2, mg = warp & 3;
    uint32_t wA[KR * 3][4];
    uint32_t wO[WR][4];
    const uint32_t swf0 = sbase + OFF_WF + (warp < 4 ? warp * NSF_LO : 4 * NSF_LO + (warp - 4) * NSF_HI) * 512 + lane * 16;
    {
      static_assert(KR == 12 && 18 * 8192 <= OFF_RT && OFF_RT % 1024 == 0 && OFF_RT + 65536 <= B_BAR, "prologue staging");
      const uint32_t wb = sbase + B_BAR + BR_WF, ring = sbase + OFF_RT;
      const int li = lane >> 3, lr = lane & 7;
      auto piece = [&](int pc) {
        const uint32_t dst = ring + (pc & 1) * 32768, bar = wb + 24 + pc * 8;
        if (pc < 3) {
          mbar_expect_tx(bar, 32768);
#pragma unroll 1
          for (int q = 0; q < 4; q++) tma_load(dst + q * 8192, &a.tmW1[pc], h * DH + j * 64, 320 * (q >> 1) + 192 + (q & 1) * 64, bar);
        } else {
          mbar_expect_tx(bar, pc < 5 ? 32768 : 16384);
          tma_load(dst, &a.tmWo1, j * 320 + (pc - 3) * 128, h * DH, bar);
          if (pc < 5) tma_load(dst + 16384, &a.tmWo1, j * 320 + (pc - 3) * 128 + 64, h * DH, bar);
        }
      };
      PST(0);
      if (tid == 0) {
        if (PRO_DELAY) __nanosleep(PRO_DELAY);
#pragma unroll 1
        for (int i = 0; i < 3; i++) {
          mbar_expect_tx(wb + i * 8, 49152);
#pragma unroll 1
          for (int q = 0; q < 6; q++) tma_load(sbase + (i * 6 + q) * 8192, &a.tmW1[q >> 1], h * DH + j * 64, 320 * (q & 1) + i * 64, wb + i * 8);
        }
        piece(0); piece(1);
      }
      PST(1);
      const uint32_t fo = ((li >> 1) * 8 + lr) * 128;
      const uint32_t qsw = fo + (((mg * 2 + (li & 1)) ^ lr) << 4);
#pragma unroll
      for (int i = 0; i < 3; i++) {
        mbar_wait(wb + i * 8, 0);
#pragma unroll
        for (int c = 0; c < 4; c++)
#pragma unroll
          for (int m = 0; m < 3; m++) ldsm4t(wA[(i * 4 + c) * 3 + m], sbase + (i * 6 + m * 2 + kg) * 8192 + c * 2048 + qsw);
      }
      bar_sync(1, 256);
      PST(3);
#pragma unroll 1
      for (int pc = 0; pc < 3; pc++) {
        mbar_wait(wb + 24 + pc * 8, 0);
#pragma unroll 2
        for (int c = 0; c < 8; c++) {
          uint32_t t[4]; ldsm4t(t, ring + (pc & 1) * 32768 + kg * 16384 + c * 2048 + qsw);
          sts128(swf0 + (c * 3 + pc) * 512, t[0], t[1], t[2], t[3]);
        }
        bar_sync(1, 256);
        if (tid == 0) { fence_proxy_async_smem(); piece(pc + 2); }
      }
      PST(4);
      auto wo_piece = [&](auto pcc, auto ntc) {
        constexpr int pc = decltype(pcc)::value, NT = decltype(ntc)::value, i = pc - 3;
        const uint32_t src = ring + (pc & 1) * 32768 + (pc < 5 ? (warp >> 2) * 16384 : 0) + qsw;
#pragma unroll
        for (int ks = 0; ks < 8; ks++) {
          const int f = ks * NT + i;
          if (f >= WF0 && f < WF0 + WR) ldsm4t(wO[f - WF0], src + ks * 2048);
          else { uint32_t t[4]; ldsm4t(t, src + ks * 2048); sts128(swf0 + (NSQ + (f < WF0 ? f : f - WR)) * 512, t[0], t[1], t[2], t[3]); }
        }
      };
      mbar_wait(wb + 24 + 3 * 8, 0);
      if (warp < 4) wo_piece(IC<3>{}, IC<3>{}); else wo_piece(IC<3>{}, IC<2>{});
      bar_sync(1, 256);
      if (tid == 0) { fence_proxy_async_smem(); piece(5); }
      mbar_wait(wb + 24 + 4 * 8, 0);
      if (warp < 4) wo_piece(IC<4>{}, IC<3>{}); else wo_piece(IC<4>{}, IC<2>{});
      mbar_wait(wb + 24 + 5 * 8, 0);
      if (warp < 4) wo_piece(IC<5>{}, IC<3>{});
      bar_sync(1, 256);
    }
    PST(5);
    bar_sync(2, 288);
    if (tid == 0) mbar_expect_tx(bar_x, 2304);
    const uint32_t peer_off = mapa(sbase, j ^ 1) - sbase;
    const float SL2E = 0.08838834764831845f * 1.4426950408889634f;
    const int rme = 32 * j + h;
    const int g = lane >> 2, c4 = lane & 3;
    uint32_t part_off[3];
#pragma unroll
    for (int i = 0; i < 3; i++) {
      const int t = i < 2 ? warp + 8 * i : 16 + (warp & 3);
      const int U = (20 * j + t) * 16 + c4 * 4 + (g >> 1);
      const int r = U / 10;
      part_off[i] = (r * 32 + h) * 80 + ((U - r * 10) * 2 + (g & 1)) * 4;
    }
    const int rch = 4 * (warp - 3) + (lane & 3);
    const uint32_t rsrc_off = (rme * 32 + (lane >> 2)) * 80 + rch * 4;
    uint32_t mdst;
    {
      mdst = (rme * 10 + (rch >> 1)) * 8 + ((lane >> 3) & 1) * 4 + ((lane >> 4) & 1) * 2 + (rch & 1);
    }
    const uint32_t kvm_off = ((kg ? NSEG * NM : 0) + g) * HD + h * DH + j * 64 + mg * 16 + 2 * c4;
    const uint32_t l16 = sbase + lane * 16;
    const uint32_t cst = l16 + OFF_CST + warp * 1024;
    sts128(cst, part_off[0], part_off[1], part_off[2], rsrc_off);
    sts128(cst + 512, mdst, kvm_off, a.dG, a.dG2);
    const uint32_t swf = swf0;
    const uint32_t mb_dst = l16 + OFF_MEMB + (kg * 10 + (mg >> 1)) * 512 + (mg & 1) * 8;
    uint32_t Q[12][4];
#pragma unroll
    for (int k = 0; k < 5; k++) {
      const int ks = kg * 20 + mg + 4 * k;
      uint32_t b0 = *(const uint32_t*)(a.mem0 + g * DM + ks * 16 + 2 * c4), b1 = *(const uint32_t*)(a.mem0 + g * DM + ks * 16 + 8 + 2 * c4);
      sts64(mb_dst + k * 1024, b0, b1);
    }
#pragma unroll
    for (int n = 0; n < 12; n++) lds128(Q[n], swf + n * 512);
    int tid_keep = tid;
#pragma unroll 1
    for (int s = 0; s < NSEG; s++) {
      const int b = s & 1;
      asm volatile("" : "+r"(tid_keep));
      const int tid = tid_keep, lane = tid & 31, warp = tid >> 5, kg = warp >> 2, mg = warp & 3;
      const uint32_t l8 = sbase + lane * 8, l16 = sbase + lane * 16;
      const uint32_t cst = l16 + OFF_CST + warp * 1024;
      const uint32_t swf = l16 + OFF_WF + (warp < 4 ? warp * NSF_LO : 4 * NSF_LO + (warp - 4) * NSF_HI) * 512;
      bar_sync(9 + kg, 128);
      STAMP(1);
      float acc[6][4];
#pragma unroll
      for (int m = 0; m < 6; m++) { acc[m][0] = acc[m][1] = acc[m][2] = acc[m][3] = 0.f; }
      {
        const uint32_t bb = l16 + OFF_MEMB + kg * 5120;
        uint32_t bf[2][4];
        lds128(bf[0], bb + 6 * 512);
#pragma unroll
        for (int i = 0; i < 10; i++) {
          const int kp = i < 2 ? 6 + i : (i < 8 ? i - 2 : i), kn = i + 1 < 2 ? 7 + i : (i + 1 < 8 ? i - 1 : i + 1);
          if (i + 1 < 10) lds128(bf[(i + 1) & 1], bb + kn * 512);
#pragma unroll
          for (int m = 0; m < 6; m++) {
            if (kp < 6) mma16816(acc[m % NACC], wA[kp * 6 + m], bf[i & 1][(m / 3) * 2], bf[i & 1][(m / 3) * 2 + 1]);
            else mma16816(acc[m % NACC], Q[((kp - 6) & 1) * 6 + m], bf[i & 1][(m / 3) * 2], bf[i & 1][(m / 3) * 2 + 1]);
          }
          if (i < 2) {
#pragma unroll
            for (int m = 0; m < 6; m++) lds128(Q[i * 6 + m], swf + ((i + 2) * 6 + m) * 512);
          }
        }
#pragma unroll
        for (int m = 0; m < 3; m++)
#pragma unroll
          for (int q = 0; q < 4; q++) if (NACC == 6) acc[m][q] += acc[m + 3][q];
      }
      STAMP(2);
      if (s == 0) mbar_wait(bar_full, 0);
      const uint32_t red = l16 + OFF_RED + mg * 1536;
      if (kg == 0) sts128(red + 1024, __float_as_uint(acc[2][0]), __float_as_uint(acc[2][1]), __float_as_uint(acc[2][2]), __float_as_uint(acc[2][3]));
      else { sts128(red, __float_as_uint(acc[0][0]), __float_as_uint(acc[0][1]), __float_as_uint(acc[0][2]), __float_as_uint(acc[0][3]));
             sts128(red + 512, __float_as_uint(acc[1][0]), __float_as_uint(acc[1][1]), __float_as_uint(acc[1][2]), __float_as_uint(acc[1][3])); }
      bf16* const kvd = &g_KVm[0][0] + (lds32(cst + 516) + s * (NM * HD));
      if (kg == 0) {
        uint32_t ka = sbase + OFF_KX + b * 4608 + (((lane >> 4) & 1) * 8 + (lane & 7)) * 144 + (mg * 16 + ((lane >> 3) & 1) * 8) * 2;
        ldsm4(Q[0], ka); ldsm4(Q[1], ka + 16 * 144);
        bar_sync(3 + mg, 64);
        lds128(Q[2], red); lds128(Q[3], red + 512);
        uint32_t q0 = movm(pack_bf16(acc[0][0] + __uint_as_float(Q[2][0]), acc[0][1] + __uint_as_float(Q[2][1]))), q1 = movm(pack_bf16(acc[0][2] + __uint_as_float(Q[2][2]), acc[0][3] + __uint_as_float(Q[2][3])));
        uint32_t k0 = movm(pack_bf16(acc[1][0] + __uint_as_float(Q[3][0]), acc[1][1] + __uint_as_float(Q[3][1]))), k1 = movm(pack_bf16(acc[1][2] + __uint_as_float(Q[3][2]), acc[1][3] + __uint_as_float(Q[3][3])));
        float sp[5][4];
#pragma unroll
        for (int t = 0; t < 5; t++) sp[t][0] = sp[t][1] = sp[t][2] = sp[t][3] = 0.f;
        mma16816_4(sp[1], q0, 0, q1, 0, Q[0][0], Q[0][1]);
        mma16816_4(sp[2], q0, 0, q1, 0, Q[0][2], Q[0][3]);
        mma16816_4(sp[3], q0, 0, q1, 0, Q[1][0], Q[1][1]);
        mma16816_4(sp[4], q0, 0, q1, 0, Q[1][2], Q[1][3]);
        mma16816_4(sp[0], q0, 0, q1, 0, k0, k1);
        const uint32_t spb = l8 + OFF_SP + mg * 1280;
#pragma unroll
        for (int t = 0; t < 5; t++) sts64(spb + t * 256, __float_as_uint(sp[t][0]), __float_as_uint(sp[t][1]));
        *(uint32_t*)kvd = k0; *(uint32_t*)(kvd + 8) = k1;
      } else {
        bar_sync(3 + mg, 64);
        lds128(Q[2], red + 1024);
        uint32_t v0 = pack_bf16(acc[2][0] + __uint_as_float(Q[2][0]), acc[2][1] + __uint_as_float(Q[2][1])), v1 = pack_bf16(acc[2][2] + __uint_as_float(Q[2][2]), acc[2][3] + __uint_as_float(Q[2][3]));
        uint32_t dst = l8 + OFF_VM + (j * 4 + mg) * 256;
        if (s < NSEG - 1) st_async_v2(dst + peer_off, v0, v1, bar_x + peer_off);
        sts64(dst, v0, v1);
        uint32_t t0 = movm(v0), t1 = movm(v1);
        *(uint32_t*)kvd = t0; *(uint32_t*)(kvd + 8) = t1;
      }
      bar_sync(1, 256);
      if (s == NSEG - 1) { if (tid == 0) mbar_arrive(bar_empty + 8 * b); break; }
      if (warp < 5) {
        uint32_t x0[2], x1[2], x2[2], x3[2];
        const uint32_t spb = l8 + OFF_SP + warp * 256;
        lds64(x0, spb); lds64(x1, spb + 1280); lds64(x2, spb + 2560); lds64(x3, spb + 3840);
        float sx = (__uint_as_float(x0[0]) + __uint_as_float(x1[0])) + (__uint_as_float(x2[0]) + __uint_as_float(x3[0]));
        float sy = (__uint_as_float(x0[1]) + __uint_as_float(x1[1])) + (__uint_as_float(x2[1]) + __uint_as_float(x3[1]));
        uint32_t dst = l8 + OFF_SX + warp * 256 + j * 1280;
        st_async_v2(dst + peer_off, __float_as_uint(sx), __float_as_uint(sy), bar_x + peer_off);
        sts64(dst, __float_as_uint(sx), __float_as_uint(sy));
        __syncwarp();
        if (lane == 0) mbar_arrive(bar_x);
      }
      STAMP(3);
      uint32_t* const gp = &g_part[b][0][0][0];
      const uint32_t tag = ((s >> 1) + 1) & 3;
      uint32_t po[4];
      uint32_t t_5;
      auto wo_phase = [&](auto ntc, auto nqc, uint32_t (*R)[4]) {
        constexpr int NT = decltype(ntc)::value, NQ = decltype(nqc)::value;
        lds128(po, cst);
        bar_sync(1, 256);
        if (tid == 0) { mbar_arrive(bar_empty + 8 * b); if (s < NSEG - 2) mbar_expect_tx(bar_x, 2304); }
        STAMP(5);
        t_5 = clk32();
        uint32_t ob[4][4];
#pragma unroll
        for (int kp = 0; kp < 4; kp++) lds128(ob[kp], l16 + OFF_O + kp * 512);
        float d[NT][2][4];
#pragma unroll
        for (int i = 0; i < NT; i++)
#pragma unroll
          for (int q = 0; q < 2; q++) d[i][q][0] = d[i][q][1] = d[i][q][2] = d[i][q][3] = 0.f;
#pragma unroll
        for (int ks = 0; ks < 8; ks++) {
          const uint32_t b0 = ob[ks >> 1][(ks & 1) * 2], b1 = ob[ks >> 1][(ks & 1) * 2 + 1];
#pragma unroll
          for (int i = 0; i < NT; i++) {
            const int f = ks * NT + i;
            if (f >= WF0 && f < WF0 + WR) mma16816(d[i][ks & 1], wO[f - WF0], b0, b1);
            else {
              const int n = f < WF0 ? f : f - WR;
              mma16816(d[i][ks & 1], R[n % NQ], b0, b1);
              if (n + NQ < NT * 8 - WR) lds128(R[n % NQ], swf + (NSQ + n + NQ) * 512);
            }
          }
        }
#pragma unroll
        for (int i = 0; i < NT; i++) {
          uint32_t w[4];
#pragma unroll
          for (int q = 0; q < 4; q++) w[q] = (__float_as_uint(d[i][0][q] + d[i][1][q]) & ~3u) | tag;
          st_relaxed_v4(gp + po[i], w[0], w[1], w[2], w[3]);
        }
      };
      if (warp >= 4) {
#pragma unroll
        for (int n = 0; n < 4; n++) lds128(Q[n], swf + (NSQ + n) * 512);
        uint32_t vx[4][4];
        {
          uint32_t va = sbase + OFF_VX + b * 8704 + (((lane >> 3) & 1) * 8 + (lane & 7)) * 272 + (mg * 32 + (lane >> 4) * 8) * 2;
          ldsm4t(vx[0], va); ldsm4t(vx[1], va + 16 * 272); ldsm4t(vx[2], va + 32); ldsm4t(vx[3], va + 16 * 272 + 32);
        }
        mbar_wait(bar_x, s & 1);
        STAMP(4);
        float p[10];
#pragma unroll
        for (int t = 0; t < 5; t++) { uint32_t u[4]; lds64(u, l8 + OFF_SX + t * 256); lds64(u + 2, l8 + OFF_SX + 1280 + t * 256);
          p[2 * t] = __uint_as_float(u[0]) + __uint_as_float(u[2]); p[2 * t + 1] = __uint_as_float(u[1]) + __uint_as_float(u[3]); }
        uint32_t vm[4]; lds64(vm, l8 + OFF_VM + mg * 512); lds64(vm + 2, l8 + OFF_VM + mg * 512 + 256);
        float mx = fmaxf(fmaxf(fmaxf(p[0], p[1]), fmaxf(p[2], p[3])), fmaxf(fmaxf(fmaxf(p[4], p[5]), fmaxf(p[6], p[7])), fmaxf(p[8], p[9])));
        mx = fmaxf(mx, __shfl_xor_sync(0xffffffffu, mx, 1)); mx = fmaxf(mx, __shfl_xor_sync(0xffffffffu, mx, 2));
        const float mxl = -mx * SL2E;
#pragma unroll
        for (int i = 2; i < 10; i++) p[i] = ex2(fmaf(p[i], SL2E, mxl));
        p[0] = ex2(fmaf(p[0], SL2E, mxl)); p[1] = ex2(fmaf(p[1], SL2E, mxl));
        uint32_t pa[5];
#pragma unroll
        for (int t = 0; t < 5; t++) pa[t] = pack_bf16(p[2 * t], p[2 * t + 1]);
        float o[4][4], o2[4][4];
#pragma unroll
        for (int q = 0; q < 4; q++) { o[q][0] = o[q][1] = o[q][2] = o[q][3] = 0.f; o2[q][0] = o2[q][1] = o2[q][2] = o2[q][3] = 0.f; }
#pragma unroll
        for (int q = 0; q < 4; q++) mma16816_4(o[q], pa[1], 0, pa[2], 0, vx[(q >> 1) * 2][(q & 1) * 2], vx[(q >> 1) * 2][(q & 1) * 2 + 1]);
#pragma unroll
        for (int q = 0; q < 4; q++) mma16816_4(o2[q], pa[3], 0, pa[4], 0, vx[(q >> 1) * 2 + 1][(q & 1) * 2], vx[(q >> 1) * 2 + 1][(q & 1) * 2 + 1]);
#pragma unroll
        for (int q = 0; q < 4; q++) mma1688(o[q], pa[0], 0, vm[q]);
        float sum = (((p[0] + p[1]) + (p[2] + p[3])) + ((p[4] + p[5]) + (p[6] + p[7]))) + (p[8] + p[9]);
        sum += __shfl_xor_sync(0xffffffffu, sum, 1); sum += __shfl_xor_sync(0xffffffffu, sum, 2);
        const float inv = rcp(sum);
        sts128(l16 + OFF_O + mg * 512, pack_bf16((o[0][0] + o2[0][0]) * inv, (o[0][1] + o2[0][1]) * inv), pack_bf16((o[1][0] + o2[1][0]) * inv, (o[1][1] + o2[1][1]) * inv),
                                       pack_bf16((o[2][0] + o2[2][0]) * inv, (o[2][1] + o2[2][1]) * inv), pack_bf16((o[3][0] + o2[3][0]) * inv, (o[3][1] + o2[3][1]) * inv));
        wo_phase(IC<2>{}, IC<4>{}, Q);
      } else {
        STAMP(4);
        uint32_t R[NQA][4];
#pragma unroll
        for (int n = 0; n < NQA; n++) lds128(R[n], swf + (NSQ + n) * 512);
        wo_phase(IC<3>{}, IC<NQA>{}, R);
      }
      STAMP(6);
      uint32_t cs[4]; lds128(cs, cst + 512);
      uint32_t* const gm = &g_memt[b ^ 1][0];
      if (warp >= 3) {
        const uint32_t* src = gp + po[3];
        while ((int)(clk32() - t_5) < (int)cs[2]) {}
        uint4 v[4];
        int adj = -ADJ_DN, tries = 0;
        while (true) {
#pragma unroll
          for (int k = 0; k < 4; k++) v[k] = ld_relaxed_v4(src + k * 8 * 80);
          uint32_t bad = 0;
#pragma unroll
          for (int k = 0; k < 4; k++) bad |= ((v[k].x ^ tag) | (v[k].y ^ tag)) | ((v[k].z ^ tag) | (v[k].w ^ tag));
          if (__all_sync(0xffffffffu, !(bad & 3))) break;
          adj = ADJ_UP;
          if ((++tries & 63) == 0 && __any_sync(0xffffffffu, expired(sbase + B_BAR))) break;
        }
        float x = (__uint_as_float(v[0].x) + __uint_as_float(v[1].x)) + (__uint_as_float(v[2].x) + __uint_as_float(v[3].x));
        float y = (__uint_as_float(v[0].y) + __uint_as_float(v[1].y)) + (__uint_as_float(v[2].y) + __uint_as_float(v[3].y));
        float z = (__uint_as_float(v[0].z) + __uint_as_float(v[1].z)) + (__uint_as_float(v[2].z) + __uint_as_float(v[3].z));
        float w = (__uint_as_float(v[0].w) + __uint_as_float(v[1].w)) + (__uint_as_float(v[2].w) + __uint_as_float(v[3].w));
        const bool h4 = lane & 16, h3 = lane & 8;
        float e0 = (h4 ? z : x) + __shfl_xor_sync(0xffffffffu, h4 ? x : z, 16);
        float e1 = (h4 ? w : y) + __shfl_xor_sync(0xffffffffu, h4 ? y : w, 16);
        float f = (h3 ? e1 : e0) + __shfl_xor_sync(0xffffffffu, h3 ? e0 : e1, 8);
        f += __shfl_xor_sync(0xffffffffu, f, 4);
        if (!(lane & 4)) st_relaxed(gm + cs[0], pack_bf16(0.f, f) | (uint32_t)(s + 1));
        sts32(cst + 520, min(max((int)cs[2] + adj, 0), 8000));
      }
      STAMP(7);
      {
#pragma unroll
        for (int n = 0; n < NQP; n++) lds128(Q[n], swf + n * 512);
        mbar_wait(bar_full + 8 * (b ^ 1), ((s + 1) >> 1) & 1);
        const uint32_t* src = gm + ((kg * 20 + mg) * 32 + lane) * 4;
        while ((int)(clk32() - t_5) < (int)cs[3]) {}
        uint4 v[5];
        const uint32_t sq = s + 1;
        int adj = -ADJ_DN, tries = 0;
        while (true) {
#pragma unroll
          for (int k = 0; k < 5; k++) v[k] = ld_relaxed_v4(src + 512 * k);
          uint32_t bad = 0;
#pragma unroll
          for (int k = 0; k < 5; k++) bad |= ((v[k].x ^ sq) | (v[k].y ^ sq)) | ((v[k].z ^ sq) | (v[k].w ^ sq));
          if (!(bad & 0xffff)) break;
          adj = ADJ_UP;
          if ((++tries & 63) == 0 && expired(sbase + B_BAR)) break;
        }
        adj = __reduce_max_sync(0xffffffffu, adj);
        asm volatile("" : "+r"(tid_keep));
        const uint32_t mb_dst = sbase + ((((tid_keep >> 3) & 3) * 2 + (tid_keep & 1)) * 4 + ((tid_keep >> 1) & 3)) * 16 + OFF_MEMB + ((tid_keep >> 7) * 10 + ((tid_keep >> 6) & 1)) * 512 + ((tid_keep >> 5) & 1) * 8;
#pragma unroll
        for (int k = 0; k < 5; k++) sts64(mb_dst + k * 1024, __byte_perm(v[k].x, v[k].y, 0x7632), __byte_perm(v[k].z, v[k].w, 0x7632));
#pragma unroll
        for (int n = NQP; n < 12; n++) lds128(Q[n], swf + n * 512);
        sts32(cst + 524, min(max((int)cs[3] + adj, 0), 8000));
      }
      STAMP(0);
    }
}

#define TLS(i)
#define DEADLINE_NS 200000000
struct Ring { uint32_t st, ph; __device__ __forceinline__ void next() { if (++st == NST) { st = 0; ph ^= 1; } } };

__device__ __forceinline__ void flag_helper(const uint32_t sbase, int wg) {
  const uint32_t jb = sbase + B_BAR + BR_JOB + wg * 32;
  for (;;) {
    bar_sync(12 + wg, 160);
    const uint32_t fl = lds32(jb);
    __syncwarp();
    if ((threadIdx.x & 31) == 0) mbar_arrive(sbase + B_BAR + BR_SFREE + 8 * wg);
    if ((int)fl < 0) break;
    if ((threadIdx.x & 31) == 0) { __threadfence(); red_release((uint32_t*)&g_f + fl, 1); }
  }
}
struct Stg { uint32_t ph; };
__device__ __forceinline__ void post_flag(Stg& sg, const uint32_t sbase, uint32_t flag, int tid) {
  const int wg = tid >> 7;
  if ((tid & 127) == 0) { mbar_wait(sbase + B_BAR + BR_SFREE + 8 * wg, sg.ph); sts32(sbase + B_BAR + BR_JOB + wg * 32, flag); }
  sg.ph ^= 1;
  __syncwarp();
  bar_arrive(12 + wg, 160);
}
__device__ __forceinline__ void warp_store64(const float* acc, const uint32_t stg, bf16* dst  , int lane) {
  const int i = lane >> 3, rr = lane & 7;
#pragma unroll
  for (int jj = 0; jj < 8; jj += 2)
    stsm4(stg + ((i & 1) * 8 + rr) * 128 + (((jj + (i >> 1)) ^ rr) << 4), pack_bf16(acc[jj * 4 + 0], acc[jj * 4 + 1]), pack_bf16(acc[jj * 4 + 2], acc[jj * 4 + 3]),
          pack_bf16(acc[jj * 4 + 4], acc[jj * 4 + 5]), pack_bf16(acc[jj * 4 + 6], acc[jj * 4 + 7]));
  __syncwarp();
  uint32_t v[4][4];
#pragma unroll
  for (int q = 0; q < 4; q++) { const int r = q * 4 + i; lds128(v[q], stg + r * 128 + ((rr ^ (r & 7)) << 4)); }
#pragma unroll
  for (int q = 0; q < 4; q++) __stcg((uint4*)(dst + (size_t)(q * 4 + i) * HD + rr * 8), make_uint4(v[q][0], v[q][1], v[q][2], v[q][3]));
  __syncwarp();
}

__device__ __forceinline__ void kv_producer(const Params& p, const uint32_t sbase, int cb) {
  const uint32_t bb = sbase + B_BAR;
  const CUtensorMap* tw = cb < 32 ? &p.tmWk : &p.tmWv;
  const int n0 = (cb & 31) * 128;
  uint32_t st = 0, ph = 1;
#pragma unroll 1
  for (int it = 0; it < 160; it++) {
    const int rb = it / 10; int kb = it - rb * 10 + cb % 10; if (kb >= 10) kb -= 10;
    if (it == 3) {
#pragma unroll 1
      for (int u = 3; u < 10; u++) { int kw = u + cb % 10; if (kw >= 10) kw -= 10;
        mbar_expect_tx(bb + BR_WF + 8 * kw, 16384); tma_load3(sbase + kw * 16384, tw, kw * 64, n0 >> 6, bb + BR_WF + 8 * kw); }
    }
    if (it < 3) {
      mbar_expect_tx(bb + BR_WF + 8 * kb, 16384);
      tma_load3(sbase + kb * 16384, tw, kb * 64, n0 >> 6, bb + BR_WF + 8 * kb);
    }
    mbar_wait<1>(bb + BR_XE + 8 * st, ph);
    const uint32_t fb = bb + BR_XF + 8 * st, sa = sbase + KV_X + st * 16384;
    mbar_expect_tx(fb, 16384);
    tma_load(sa, &p.tmX, kb * 64, rb * 128, fb);
    if (++st == 3) { st = 0; ph ^= 1; }
  }
}
__device__ __forceinline__ void kv_consumer(const Params& p, Stg& sg, const uint32_t sbase, int cb) {
  const int tid = opaque_tid(), wg = tid >> 7;
  const bool elect = (tid & 127) == 0;
  const uint32_t bb = sbase + B_BAR;
#pragma unroll 1
  for (int rb = wg; rb < 16; rb += 2) {
    float acc[128];
#pragma unroll
    for (int i = 0; i < 128; i++) acc[i] = 0.f;
    int it = rb * 10;
    uint32_t st = it % 3, ph = (it / 3) & 1;
    if (rb > 0) bar_sync(14 + wg, 256);
    uint32_t prev = 0;
    if (cb == 7 && rb < 4) TLS(4080 + rb * 4);
#pragma unroll 1
    for (int ki = 0; ki < 10; ki++) {
      if (cb == 7 && rb == 0 && ki == 1) TLS(4080 + 1);
      int kb = ki + cb % 10; if (kb >= 10) kb -= 10;
      if (rb < 2) mbar_wait(bb + BR_WF + 8 * kb, 0);
      mbar_wait(bb + BR_XF + 8 * st, ph);
      if (ki == 9 && rb < 15) bar_arrive(14 + (wg ^ 1), 256);
      const uint64_t da = make_desc(sbase + KV_X + st * 16384, 16, 1024);
      const uint64_t db = make_desc(sbase + kb * 16384, 8192, 1024);
      wg_fence();
#pragma unroll
      for (int k = 0; k < 4; k++) { wgmma_n128(acc, da + k * 2, db + k * 128); wgmma_n128(acc + 64, da + 512 + k * 2, db + k * 128); }
      wg_commit();
      if (ki > 0) { wg_wait<1>(); if (elect) mbar_arrive(bb + BR_XE + 8 * prev); }
      prev = st;
      if (++st == 3) { st = 0; ph ^= 1; }
    }
    wg_wait<0>();
    if (elect) mbar_arrive(bb + BR_XE + 8 * prev);
    if (cb == 7 && rb < 4) TLS(4080 + rb * 4 + 2);
    const uint32_t stg = sbase + KV_STG + (tid >> 5) * 2048;
    bf16* dst = &g_KV[(cb >> 5) * SEQ + rb * 128 + ((tid >> 5) & 3) * 16][(cb & 31) * 128];
    warp_store64(acc, stg, dst, tid & 31);
    warp_store64(acc + 32, stg, dst + 64, tid & 31);
    warp_store64(acc + 64, stg, dst + 64 * HD, tid & 31);
    warp_store64(acc + 96, stg, dst + 64 * HD + 64, tid & 31);
    post_flag(sg, sbase, (uint32_t)(offsetof(Flags, kv) / 4) + rb * 64 + cb, tid);
    if (cb == 7 && rb < 4) TLS(4080 + rb * 4 + 3);
  }
}

__device__ __forceinline__ void bulk_producer(const Params& p, const uint32_t sbase) {
  Ring r{0, 1};
  const uint32_t bb = sbase + B_BAR;
  for (int it = 0;; it++) {
    const int slot = it & 1;
    mbar_wait<1>(bb + BR_TQE + 8 * slot, ((it >> 1) & 1) ^ 1);
    int t = p.t_begin + (int)atomicAdd(&g_f.task_ctr, 1u);
    if (t >= p.t_end) t = N_TASKS;
    sts32(bb + BR_TASK + 4 * slot, t);
    mbar_arrive(bb + BR_TQF + 8 * slot);
    if (t >= N_TASKS) break;
    int rb, q, kcn; const int kind = decode(t, rb, q, kcn);
    if (kind < K_QA) {
      mbar_wait<1>(bb + BR_TQE + 8 * slot, (it >> 1) & 1);
    } else {
      if (kind == K_QA) {
#pragma unroll 1
        for (int kb = 0; kb < 10; kb++) {
          mbar_wait<1>(bb + BR_EMPTY + 8 * r.st, r.ph);
          const uint32_t fb = bb + BR_FULL + 8 * r.st, sa = sbase + r.st * STAGE;
          mbar_expect_tx(fb, 49152);
          tma_load(sa, &p.tmX, kb * 64, rb * 128, fb);
          tma_load3(sa + 16384, &p.tmWq, kb * 64, q * 4, fb);
          r.next();
        }
#pragma unroll 1
        for (int u = 0; u < 4; u++) {
          const int h = 2 * q + (u >> 1), kv = u & 1;
          wait_flag(sbase + B_BAR, &g_f.kv[rb][kv * 32 + h], 1);
          if (kv == 0) { wait_flag(sbase + B_BAR, &g_f.prog[2 * h][0], 4 * rb + 4); wait_flag(sbase + B_BAR, &g_f.prog[2 * h + 1][0], 4 * rb + 4); }
          fence_proxy_async();
          mbar_wait<1>(bb + BR_EMPTY + 8 * r.st, r.ph);
          const uint32_t fb = bb + BR_FULL + 8 * r.st, sa = sbase + r.st * STAGE;
          mbar_expect_tx(fb, 40960);
          tma_load3(sa, &p.tmKVl, kv * SEQ + rb * 128, h * 2, fb);
          tma_load3(sa + 32768, &p.tmKVm, kv * 512 + rb * 32, h * 2, fb);
          r.next();
        }
      } else {
        const bool fine = kcn == 16;
        if (fine) kcn = FKC;
        const int ct = fine ? q / FKC : q & 1, kc = fine ? q % FKC : q >> 1, nkb = 64 / kcn;
#pragma unroll 1
        for (int u = 0; u < 16 / kcn; u++) wait_flag(sbase + B_BAR, &g_f.o_rdy[rb][kc * (16 / kcn) + u], 4);
        fence_proxy_async();
#pragma unroll 1
        for (int kb = 0; kb < nkb; kb++) {
          mbar_wait<1>(bb + BR_EMPTY + 8 * r.st, r.ph);
          const uint32_t fb = bb + BR_FULL + 8 * r.st, sa = sbase + r.st * STAGE;
          mbar_expect_tx(fb, fine ? 32768 : 57344);
          const int k0 = (kc * nkb + kb) * 64;
          tma_load(sa, &p.tmOl, k0, rb * 128, fb);
          tma_load3(sa + 16384, fine ? &p.tmWo2 : &p.tmWo, k0, fine ? ct * 2 : ct * 5, fb);
          r.next();
        }
        if (kcn > 2) mbar_wait<1>(bb + BR_TQE + 8 * slot, (it >> 1) & 1);
      }
    }
  }
}

template<int N>
__device__ __forceinline__ void gemm_mainloop(float* acc, Ring& r, const uint32_t sbase, int nkb, int wg, bool elect) {
  const uint32_t bb = sbase + B_BAR;
#pragma unroll
  for (int i = 0; i < N / 2; i++) acc[i] = 0.f;
#pragma unroll 1
  for (int kb = 0; kb < nkb; kb++) {
    mbar_wait(bb + BR_FULL + 8 * r.st, r.ph);
    const uint32_t sa = sbase + r.st * STAGE;
    const uint64_t da = make_desc(sa + wg * 8192, 16, 1024);
    const uint64_t db = make_desc(sa + 16384, 8192, 1024);
    wg_fence();
#pragma unroll
    for (int k = 0; k < 4; k++) {
      if (N == 256) wgmma_n256(acc, da + k * 2, db + k * 128);
      else if (N == 128) wgmma_n128(acc, da + k * 2, db + k * 128);
      else { wgmma_n192(acc, da + k * 2, db + k * 128); wgmma_n128(acc + 96, da + k * 2, db + 1536 + k * 128); }
    }
    wg_commit();
    wg_wait<0>();
    if (elect) mbar_arrive(bb + BR_EMPTY + 8 * r.st);
    r.next();
  }
}

__device__ __forceinline__ uint32_t u2get(const uint2& v, int i) { return i == 0 ? v.x : v.y; }
constexpr int TP = 260;
__device__ __forceinline__ void task_prep(const Params& p, const uint32_t sbase, int rb) {
  const int tid = opaque_tid(), lane = tid & 31, warp = tid >> 5;
  const int r0 = rb * 128 + warp * 16;
#pragma unroll 1
  for (int k = 0; k < 5; k++) {
    const int d = (lane + 32 * k) * 4;
    uint2 kw[19], vw[16];
#pragma unroll
    for (int q = 0; q < 19; q++) kw[q] = (r0 - 3 + q >= 0) ? __ldg((const uint2*)(p.bk + (size_t)(r0 - 3 + q) * DM + d)) : make_uint2(0, 0);
#pragma unroll
    for (int q = 0; q < 16; q++) vw[q] = __ldg((const uint2*)(p.bv + (size_t)(r0 + q) * DM + d));
    const uint4 s0 = __ldg((const uint4*)(p.shift_k + d * 4)), s1 = __ldg((const uint4*)(p.shift_k + d * 4 + 8));
#pragma unroll
    for (int c = 0; c < 2; c++) {
      const uint4 s4 = c ? s1 : s0;
      const uint32_t tp[4] = {__byte_perm(s4.x, s4.z, 0x5410), __byte_perm(s4.x, s4.z, 0x7632), __byte_perm(s4.y, s4.w, 0x5410), __byte_perm(s4.y, s4.w, 0x7632)};
#pragma unroll
      for (int i0 = 0; i0 < 16; i0 += 2) {
        uint32_t kv[2];
#pragma unroll
        for (int i = 0; i < 2; i++) {
          uint32_t s = bmul2(u2get(kw[i0 + i], c), tp[3]);
#pragma unroll
          for (int q = 1; q < 4; q++) s = badd2(s, bmul2(u2get(kw[i0 + i + q], c), tp[3 - q]));
          kv[i] = bmul2(s, u2get(vw[i0 + i], c));
        }
        const uint32_t a = sbase + (d + 2 * c) * TP + (warp * 16 + i0) * 2;
        sts32(a, __byte_perm(kv[0], kv[1], 0x5410)); sts32(a + TP, __byte_perm(kv[0], kv[1], 0x7632));
      }
    }
  }
  {
    uint2 gw[5];
#pragma unroll
    for (int k = 0; k < 5; k++) gw[k] = __ldg((const uint2*)(p.gate_w + (lane + 32 * k) * 4));
#pragma unroll 1
    for (int i0 = 0; i0 < 16; i0 += 8) {
      uint2 xv[8][5];
#pragma unroll
      for (int i = 0; i < 8; i++)
#pragma unroll
        for (int k = 0; k < 5; k++) xv[i][k] = __ldg((const uint2*)(p.x + (size_t)(r0 + i0 + i) * DM + (lane + 32 * k) * 4));
      float s[8];
#pragma unroll
      for (int i = 0; i < 8; i++) {
        s[i] = 0.f;
#pragma unroll
        for (int k = 0; k < 5; k++) {
          const uint32_t m0 = bmul2(xv[i][k].x, gw[k].x), m1 = bmul2(xv[i][k].y, gw[k].y);
          s[i] += (bflo(m0) + bfhi(m0)) + (bflo(m1) + bfhi(m1));
        }
      }
#pragma unroll
      for (int i = 0; i < 4; i++) { const bool hi = lane & 4; const float a = hi ? s[i + 4] : s[i], b = hi ? s[i] : s[i + 4]; s[i] = a + __shfl_xor_sync(0xffffffffu, b, 4); }
#pragma unroll
      for (int i = 0; i < 2; i++) { const bool hi = lane & 2; const float a = hi ? s[i + 2] : s[i], b = hi ? s[i] : s[i + 2]; s[i] = a + __shfl_xor_sync(0xffffffffu, b, 2); }
      { const bool hi = lane & 1; const float a = hi ? s[1] : s[0], b = hi ? s[0] : s[1]; s[0] = a + __shfl_xor_sync(0xffffffffu, b, 1); }
      s[0] += __shfl_xor_sync(0xffffffffu, s[0], 8); s[0] += __shfl_xor_sync(0xffffffffu, s[0], 16);
      if (lane < 8) g_gate[r0 + i0 + lane] = bf16r(rcp(1.0f + ex2(-1.4426950408889634f * bf16r(s[0]))));
    }
  }
  bar_sync(1, 256);
#pragma unroll 4
  for (int d = warp; d < DM; d += 8) {
    const uint32_t a = sbase + d * TP + lane * 8;
    *(uint2*)(&g_kvT[d][rb * 128 + lane * 4]) = make_uint2(lds32(a), lds32(a + 4));
  }
  fence_proxy_async_smem();
  bar_sync(1, 256);
  if (tid == 0) { __threadfence(); red_release(&g_f.prep, 1); }
}
__device__ __forceinline__ void task_post(const Params& p, const uint32_t sbase, int rb) {
  const int tid = opaque_tid(), lane = tid & 31, warp = tid >> 5;
  if (tid == 0) wait_flag(sbase + B_BAR, &g_f.conv, 80 * 8);
  bar_sync(1, 256);
#pragma unroll 1
  for (int d0 = warp; d0 < DM; d0 += 320) {
    uint2 v[40];
#pragma unroll
    for (int q = 0; q < 40; q++) v[q] = __ldcg((const uint2*)(&g_ybT[d0 + q * 8][rb * 128 + lane * 4]));
#pragma unroll
    for (int q = 0; q < 40; q++) { const uint32_t a = sbase + (d0 + q * 8) * TP + lane * 8; sts32(a, v[q].x); sts32(a + 4, v[q].y); }
  }
  bar_sync(1, 256);
#pragma unroll 1
  for (int it = 0; it < 5; it++) {
    const int d = (lane + 32 * it) * 4, rl = warp * 16;
    uint2 xv[16];
#pragma unroll
    for (int i = 0; i < 16; i++) xv[i] = __ldg((const uint2*)(p.x + (size_t)(rb * 128 + rl + i) * DM + d));
#pragma unroll
    for (int i = 0; i < 16; i += 2) {
      const uint2 x0 = xv[i], x1 = xv[i + 1];
      const uint32_t a = sbase + d * TP + (rl + i) * 2;
      const uint32_t y0 = lds32(a), y1 = lds32(a + TP), y2 = lds32(a + 2 * TP), y3 = lds32(a + 3 * TP);
      *(uint2*)(&g_B[rb * 128 + rl + i][d]) = make_uint2(bmul2(x0.x, __byte_perm(y0, y1, 0x5410)), bmul2(x0.y, __byte_perm(y2, y3, 0x5410)));
      *(uint2*)(&g_B[rb * 128 + rl + i + 1][d]) = make_uint2(bmul2(x1.x, __byte_perm(y0, y1, 0x7632)), bmul2(x1.y, __byte_perm(y2, y3, 0x7632)));
    }
  }
  fence_proxy_async_smem();
  bar_sync(1, 256);
  if (tid == 0) { __threadfence(); red_release(&g_f.post[rb], 1); }
}

constexpr int CV_U = 0, CV_UCH = 5120;
constexpr int CV_W = 8 * CV_UCH, CV_WCH = 9216;
__device__ __forceinline__ void conv_mma(float (&acc)[4][4][4], uint32_t (&e)[15], const uint32_t ub, const uint32_t wb, int lane) {
#pragma unroll 1
  for (int m = 0; m < 32; m++) {
#pragma unroll
    for (int i = 0; i < 7; i++) e[i] = e[i + 8];
#pragma unroll
    for (int i = 7; i < 15; i++) e[i] = lds32(wb + (8 * m + i - 7) * 32);
    const int jr = 8 + (lane & 7) - m;
    const uint32_t ba = ub + jr * 128 + (((lane >> 3) ^ (jr & 7)) << 4);
#pragma unroll
    for (int nt = 3; nt >= 0; nt--) {
      if (nt < (m >> 3)) break;
      uint32_t b0[4], b1[4];
      ldsm4(b0, ba + nt * 1024); ldsm4(b1, (ba ^ 64) + nt * 1024);
#pragma unroll
      for (int ks = 0; ks < 4; ks++) {
        const uint32_t x0 = ks < 2 ? b0[(ks & 1) * 2] : b1[(ks & 1) * 2], x1 = ks < 2 ? b0[(ks & 1) * 2 + 1] : b1[(ks & 1) * 2 + 1];
#pragma unroll
        for (int mt = 0; mt < 4; mt++) {
          const int c = 2 * (mt - ks) + 7;
          mma16816_4(acc[mt][nt], e[c], e[c + 1], e[c - 1], e[c], x0, x1);
        }
      }
    }
  }
}

__device__ __forceinline__ void task_conv(const Params& p, uint32_t& cvph, const uint32_t sbase, int ci) {
  const int tid = opaque_tid(), lane = tid & 31, warp = tid >> 5;
  const int d = ci * 8 + warp;
  const uint32_t ub = sbase + CV_U + warp * CV_UCH, wb0 = sbase + CV_W + warp * CV_WCH;
  const uint32_t bar = sbase + B_BAR + BR_CV;
  TLS(3600 + ci * 5);
  if (tid == 0) {
    wait_flag(sbase + B_BAR, &g_f.prep, 16);
    fence_proxy_async();
    mbar_expect_tx(bar, 8 * 4096);
#pragma unroll 1
    for (int c = 0; c < 8; c++) tma_load(sbase + CV_U + c * CV_UCH + 1024, &p.tmKT, 0, (ci * 8 + c) * 32, bar);
  }
  sts128(ub + lane * 16, 0, 0, 0, 0); sts128(ub + 512 + lane * 16, 0, 0, 0, 0);
  if (lane < 16) sts128(wb0 + lane * 16, 0, 0, 0, 0);
  {
    const bf16* kf = p.ssm_k + (size_t)d * SEQ;
#pragma unroll 1
    for (int q0 = 0; q0 < 8; q0 += 4) {
      uint4 fv[4]; uint32_t fp[4];
#pragma unroll
      for (int q = 0; q < 4; q++) { const int i = lane + 32 * (q0 + q); fv[q] = __ldg((const uint4*)(kf + i * 8)); fp[q] = i ? (uint32_t)__ldg((const unsigned short*)(kf + i * 8 - 1)) : 0u; }
#pragma unroll
      for (int q = 0; q < 4; q++) {
        const uint4 v = fv[q];
        const uint32_t a = wb0 + (64 + (lane + 32 * (q0 + q)) * 8) * 4;
        sts128(a, (v.x & 0xffff) | (fp[q] << 16), __byte_perm(v.x, v.x, 0x1032), __byte_perm(v.y, v.x, 0x7610), __byte_perm(v.y, v.y, 0x1032));
        sts128(a + 16, __byte_perm(v.z, v.y, 0x7610), __byte_perm(v.z, v.z, 0x1032), __byte_perm(v.w, v.z, 0x7610), __byte_perm(v.w, v.w, 0x1032));
      }
    }
  }
  __syncwarp();
  mbar_wait(bar, cvph); cvph ^= 1;
  TLS(3600 + ci * 5 + 1);
  {
    const int g = lane >> 2, c4 = lane & 3;
    float acc[4][4][4];
#pragma unroll
    for (int a = 0; a < 4; a++)
#pragma unroll
      for (int b = 0; b < 4; b++) acc[a][b][0] = acc[a][b][1] = acc[a][b][2] = acc[a][b][3] = 0.f;
    const uint32_t wb = wb0 + (64 + g - 2 * c4) * 4;
    uint32_t e[15];
#pragma unroll
    for (int i = 8; i < 15; i++) e[i] = lds32(wb + (i - 15) * 32);
    conv_mma(acc, e, ub, wb, lane);
    __syncwarp();
    TLS(3600 + ci * 5 + 2);
#pragma unroll
    for (int nt = 0; nt < 4; nt++)
#pragma unroll
      for (int mp = 0; mp < 2; mp++)
        stsm4t(wb0 + (nt * 8 + (lane & 7)) * 128 + (((mp * 4 + (lane >> 3)) ^ (lane & 7)) << 4), pack_bf16(acc[2 * mp][nt][0], acc[2 * mp][nt][1]), pack_bf16(acc[2 * mp][nt][2], acc[2 * mp][nt][3]),
               pack_bf16(acc[2 * mp + 1][nt][0], acc[2 * mp + 1][nt][1]), pack_bf16(acc[2 * mp + 1][nt][2], acc[2 * mp + 1][nt][3]));
  }
  __syncwarp();
  TLS(3600 + ci * 5 + 3);
  {
    const uint32_t dd = (uint32_t)__ldg((const unsigned short*)(p.ssm_D + d)) * 0x10001u;
#pragma unroll 1
    for (int q = 0; q < 8; q++) {
      uint32_t k4[4], y4[4];
      const uint32_t o = (lane + 32 * q) * 16;
      lds128(k4, ub + 1024 + o); lds128(y4, wb0 + o);
#pragma unroll
      for (int i = 0; i < 4; i++) y4[i] = badd2(y4[i], bmul2(k4[i], dd));
      sts128(wb0 + o, y4[0], y4[1], y4[2], y4[3]);
    }
  }
  fence_proxy_async_smem();
  __syncwarp();
  if (lane == 0) {
    tma_store(&p.tmYT, wb0, 0, d * 32);
    tma_commit(); tma_wait0(); fence_proxy_async(); __threadfence(); red_release(&g_f.conv, 1);
  }
  TLS(3600 + ci * 5 + 4);
  bar_sync(1, 256);
}

__device__ __forceinline__ void task_qa(const Params& p, Ring& r, Stg& sg, const uint32_t sbase, int rb, int hp) {
  const int tid = opaque_tid(), lane = tid & 31, wg = tid >> 7, warp = tid >> 5;
  const bool elect = (tid & 127) == 0;
  const uint32_t bb = sbase + B_BAR;
  const int g = lane >> 2, c4 = lane & 3;
  uint32_t qa[16][4];
  {
    float acc[128];
    gemm_mainloop<256>(acc, r, sbase, 10, wg, elect);
#pragma unroll
    for (int ks = 0; ks < 16; ks++) {
      qa[ks][0] = pack_bf16(acc[ks * 8 + 0], acc[ks * 8 + 1]); qa[ks][1] = pack_bf16(acc[ks * 8 + 2], acc[ks * 8 + 3]);
      qa[ks][2] = pack_bf16(acc[ks * 8 + 4], acc[ks * 8 + 5]); qa[ks][3] = pack_bf16(acc[ks * 8 + 6], acc[ks * 8 + 7]);
    }
  }
  const int seg = warp >> 1, half = warp & 1;
  const int rr = lane & 7, i = lane >> 3;
#pragma unroll 1
  for (int hh = 0; hh < 2; hh++) {
    float sc[5][4];
#pragma unroll
    for (int t = 0; t < 5; t++) sc[t][0] = sc[t][1] = sc[t][2] = sc[t][3] = 0.f;
    {
      mbar_wait(bb + BR_FULL + 8 * r.st, r.ph);
      const uint32_t sa = sbase + r.st * STAGE;
#pragma unroll
      for (int ks = 0; ks < 8; ks++) {
        const int eh = ks >> 2, chunk = (ks & 3) * 2 + (i & 1);
        uint32_t kx[4];
        ldsm4(kx, sa + eh * 16384 + (seg * 32 + (i >> 1) * 8 + rr) * 128 + ((chunk ^ rr) << 4));
        mma16816(sc[1], qa[ks], kx[0], kx[1]);
        mma16816(sc[2], qa[ks], kx[2], kx[3]);
        if (half) {
          ldsm4(kx, sa + eh * 16384 + (seg * 32 + 16 + (i >> 1) * 8 + rr) * 128 + ((chunk ^ rr) << 4));
          mma16816(sc[3], qa[ks], kx[0], kx[1]);
          mma16816(sc[4], qa[ks], kx[2], kx[3]);
        }
        if ((ks & 1) == 0) {
          const int ch2 = (ks & 3) * 2 + i;
          ldsm4(kx, sa + 32768 + eh * 4096 + (seg * 8 + rr) * 128 + ((ch2 ^ rr) << 4));
          mma16816(sc[0], qa[ks], kx[0], kx[1]);
          mma16816(sc[0], qa[ks + 1], kx[2], kx[3]);
        }
      }
      bar_sync(7 + wg, 128);
      if (elect) mbar_arrive(bb + BR_EMPTY + 8 * r.st);
      r.next();
    }
#pragma unroll
    for (int ks = 0; ks < 8; ks++) { qa[ks][0] = qa[ks + 8][0]; qa[ks][1] = qa[ks + 8][1]; qa[ks][2] = qa[ks + 8][2]; qa[ks][3] = qa[ks + 8][3]; }
    uint32_t pa[5][2];
    {
      const float scale = 0.08838834764831845f, L2E = 1.4426950408889634f;
#pragma unroll
      for (int rh = 0; rh < 2; rh++) {
        const int row = half * 16 + rh * 8 + g;
        float v[10];
#pragma unroll
        for (int t = 0; t < 5; t++) {
          uint32_t pk = pack_bf16(sc[t][rh * 2], sc[t][rh * 2 + 1]);
          pk = pack_bf16(bflo(pk) * scale, bfhi(pk) * scale);
          v[2 * t] = bflo(pk); v[2 * t + 1] = bfhi(pk);
          if (t > 0) { const int key = (t - 1) * 8 + 2 * c4; if (key > row) v[2 * t] = -1e9f; if (key + 1 > row) v[2 * t + 1] = -1e9f; }
        }
        float mx = v[0];
#pragma unroll
        for (int q = 1; q < 10; q++) mx = fmaxf(mx, v[q]);
        mx = fmaxf(mx, __shfl_xor_sync(0xffffffffu, mx, 1)); mx = fmaxf(mx, __shfl_xor_sync(0xffffffffu, mx, 2));
        float sum = 0.f;
#pragma unroll
        for (int q = 0; q < 10; q++) { v[q] = ex2((v[q] - mx) * L2E); sum += v[q]; }
        sum += __shfl_xor_sync(0xffffffffu, sum, 1); sum += __shfl_xor_sync(0xffffffffu, sum, 2);
        const float inv = rcp(sum);
#pragma unroll
        for (int t = 0; t < 5; t++) pa[t][rh] = pack_bf16(v[2 * t] * inv, v[2 * t + 1] * inv);
      }
    }
    float acc[64];
#pragma unroll
    for (int q = 0; q < 64; q++) acc[q] = 0.f;
    {
      mbar_wait(bb + BR_FULL + 8 * r.st, r.ph);
      const uint32_t sa = sbase + r.st * STAGE;
#pragma unroll
      for (int np = 0; np < 8; np++) {
        const int eh = np >> 2, chunk = (np & 3) * 2 + (i >> 1);
        uint32_t vx[4];
        ldsm4t(vx, sa + eh * 16384 + (seg * 32 + (i & 1) * 8 + rr) * 128 + ((chunk ^ rr) << 4));
        mma16816_4(acc + np * 8, pa[1][0], pa[1][1], pa[2][0], pa[2][1], vx[0], vx[1]);
        mma16816_4(acc + np * 8 + 4, pa[1][0], pa[1][1], pa[2][0], pa[2][1], vx[2], vx[3]);
        if (half) {
          ldsm4t(vx, sa + eh * 16384 + (seg * 32 + 16 + (i & 1) * 8 + rr) * 128 + ((chunk ^ rr) << 4));
          mma16816_4(acc + np * 8, pa[3][0], pa[3][1], pa[4][0], pa[4][1], vx[0], vx[1]);
          mma16816_4(acc + np * 8 + 4, pa[3][0], pa[3][1], pa[4][0], pa[4][1], vx[2], vx[3]);
        }
        if ((np & 1) == 0) {
          const int ch2 = (np & 3) * 2 + i;
          ldsm4t(vx, sa + 32768 + eh * 4096 + (seg * 8 + rr) * 128 + ((ch2 ^ rr) << 4));
          mma1688(acc + np * 8, pa[0][0], pa[0][1], vx[0]);
          mma1688(acc + np * 8 + 4, pa[0][0], pa[0][1], vx[1]);
          mma1688(acc + np * 8 + 8, pa[0][0], pa[0][1], vx[2]);
          mma1688(acc + np * 8 + 12, pa[0][0], pa[0][1], vx[3]);
        }
      }
      bar_sync(7 + wg, 128);
      if (elect) mbar_arrive(bb + BR_EMPTY + 8 * r.st);
      r.next();
    }
    const int h = 2 * hp + hh;
    bf16* dst = &g_O[rb * 128 + warp * 16][h * 128];
    warp_store64(acc, sbase + B_STG + warp * 2048, dst, lane);
    warp_store64(acc + 32, sbase + B_STG + warp * 2048, dst + 64, lane);
    post_flag(sg, sbase, (uint32_t)(offsetof(Flags, o_rdy) / 4) + rb * 16 + hp, tid);
  }
}

__device__ __forceinline__ uint32_t mix2(float a0, float a1, uint32_t bv, uint32_t gt, uint32_t og) {
  return badd2(bmul2(gt, pack_bf16(a0, a1)), bmul2(og, bv));
}
template<int N>
__device__ __forceinline__ void op_partial(Ring& r, const uint32_t sbase, float* tile  , int nkb, int tid) {
  const int lane = tid & 31, wg = tid >> 7, wq = (tid >> 5) & 3;
  float acc[N / 2];
  gemm_mainloop<N>(acc, r, sbase, nkb, wg, (tid & 127) == 0);
  float* dst = tile + (wg * 64 + wq * 16 + (lane >> 2)) * DM + 2 * (lane & 3);
#pragma unroll
  for (int j = 0; j < N / 8; j++) {
    __stcg((float2*)(dst + j * 8), make_float2(acc[j * 4], acc[j * 4 + 1]));
    __stcg((float2*)(dst + 8 * DM + j * 8), make_float2(acc[j * 4 + 2], acc[j * 4 + 3]));
  }
}
__device__ __forceinline__ void task_op(const Params& p, Ring& r, const uint32_t sbase, int rb, int q, int kcn) {
  const int tid = opaque_tid();
  const bool fine = kcn == 16;
  if (fine) kcn = FKC;
  const int ct = fine ? q / FKC : q & 1, kc = fine ? q % FKC : q >> 1;
  const int col0 = fine ? ct * 128 : ct * 320, c4n = fine ? 32 : 80;
  const float* pbase = fine ? &g_PF[rb & 1][0][0][0] : &g_P[0][rb * 128][0];
  const size_t pstride = fine ? (size_t)128 * DM : (size_t)SEQ * DM;
  if (fine) op_partial<128>(r, sbase, (float*)pbase + kc * pstride + col0, 64 / FKC, tid);
  else op_partial<320>(r, sbase, (float*)pbase + kc * pstride + col0, 64 / kcn, tid);
  bar_sync(1, 256);
  if (tid == 0) {
    __threadfence();
    const uint32_t tk = atomicAdd(&g_f.op_wr[rb][ct], 1u);
    const bool fin = kcn > 2 || tk == 1;
    if (fin) { wait_flag(sbase + B_BAR, &g_f.op_wr[rb][ct], kcn); wait_flag(sbase + B_BAR, &g_f.post[rb], 1); }
    sts32(sbase + B_BAR + BR_MISC, fin);
  }
  bar_sync(1, 256);
  if (lds32(sbase + B_BAR + BR_MISC)) {
    const int row0 = kcn > 2 ? kc * (128 / kcn) : 0, nel = (kcn > 2 ? 128 / kcn : 128) * c4n;
#pragma unroll 1
    for (int u = tid; u < nel; u += 5 * 256) {
      float4 s[5]; uint2 bv[5]; float gt[5]; int o[5];
#pragma unroll
      for (int i = 0; i < 5; i++) {
        const int idx = min(u + i * 256, nel - 1), row = row0 + idx / c4n;
        o[i] = row * DM + col0 + (idx % c4n) * 4;
        s[i] = __ldcg((const float4*)(pbase + o[i]));
        bv[i] = __ldcg((const uint2*)(&g_B[rb * 128][0] + o[i]));
        gt[i] = __ldcg(&g_gate[rb * 128 + row]);
      }
      if (fine && FKC == 16) {
#pragma unroll 1
        for (int q0 = 1; q0 < 16; q0 += 5) {
          float4 w[5];
#pragma unroll
          for (int i = 0; i < 5; i++) w[i] = __ldcg((const float4*)(pbase + (q0 + i) * pstride + o[0]));
#pragma unroll
          for (int i = 0; i < 5; i++) { s[0].x += w[i].x; s[0].y += w[i].y; s[0].z += w[i].z; s[0].w += w[i].w; }
        }
      } else {
#pragma unroll 1
        for (int q0 = 1; q0 < kcn; q0++) {
          float4 w[5];
#pragma unroll
          for (int i = 0; i < 5; i++) w[i] = __ldcg((const float4*)(pbase + q0 * pstride + o[i]));
#pragma unroll
          for (int i = 0; i < 5; i++) { s[i].x += w[i].x; s[i].y += w[i].y; s[i].z += w[i].z; s[i].w += w[i].w; }
        }
      }
#pragma unroll
      for (int i = 0; i < 5; i++) {
        const uint32_t g2 = pack_bf16(gt[i], gt[i]), og = pack_bf16(1.0f - gt[i], 1.0f - gt[i]);
        if (u + i * 256 < nel) *(uint2*)(p.out + rb * 128 * DM + o[i]) = make_uint2(mix2(s[i].x, s[i].y, bv[i].x, g2, og), mix2(s[i].z, s[i].w, bv[i].y, g2, og));
      }
    }
  }
}

__device__ __forceinline__ void bulk_consumer(const Params& p, Stg& sg, const uint32_t sbase) {
  Ring r{0, 0};
  uint32_t cvph = 0;
  const uint32_t bb = sbase + B_BAR;
  for (int it = 0;; it++) {
    const int slot = it & 1;
    mbar_wait(bb + BR_TQF + 8 * slot, (it >> 1) & 1);
    const int t = (int)lds32(bb + BR_TASK + 4 * slot);
    if (t >= N_TASKS) break;
    int rb, q, kcn; const int kind = decode(t, rb, q, kcn);
    if (kind == K_PREP) task_prep(p, sbase, rb);
    else if (kind == K_CONV) task_conv(p, cvph, sbase, q);
    else if (kind == K_POST) task_post(p, sbase, rb);
    else if (kind == K_QA) task_qa(p, r, sg, sbase, rb, q);
    else task_op(p, r, sbase, rb, q, kcn);
    bar_sync(7 + (threadIdx.x >> 7), 128);
    if ((threadIdx.x & 127) == 0) mbar_arrive(bb + BR_TQE + 8 * slot);
  }
}

__global__ void __cluster_dims__(2, 1, 1) __launch_bounds__(384, 1) mega_kernel(const __grid_constant__ Params p) {
  extern __shared__ __align__(1024) unsigned char sm[];
  const int tid = threadIdx.x, warp = tid >> 5;
  const uint32_t sbase = smem_u32(sm);
  const uint32_t bb = sbase + B_BAR;
  const bool is_chain = p.do_chain && blockIdx.x < 64;
  const int kvb = (int)blockIdx.x - (p.do_chain ? 64 : 0);
  const bool is_kv = p.do_kv && !is_chain && kvb < 64;
  if (tid == 0) {
    for (int i = 0; i < NST; i++) { mbar_init(bb + BR_FULL + 8 * i, 1); mbar_init(bb + BR_EMPTY + 8 * i, 2); mbar_init(bb + BR_XF + 8 * i, 1); mbar_init(bb + BR_XE + 8 * i, 1); }
    for (int i = 0; i < 2; i++) { mbar_init(bb + BR_TQF + 8 * i, 1); mbar_init(bb + BR_TQE + 8 * i, 2); mbar_init(bb + BR_KVF + 8 * i, 32); mbar_init(bb + BR_KVE + 8 * i, 1); mbar_init(bb + BR_SFREE + 8 * i, 1); }
    for (int i = 0; i < 10; i++) mbar_init(bb + BR_WF + 8 * i, 1);
    mbar_init(bb + BR_X, 6); mbar_init(bb + BR_CV, 1);
    { uint32_t t; asm volatile("mov.u32 %0, %%globaltimer_lo;" : "=r"(t)); sts32(bb + 1016, t + DEADLINE_NS); }
    asm volatile("fence.mbarrier_init.release.cluster;" ::: "memory");
  }
  __syncthreads();
  cluster_sync_all();
  if (warp >= 8) {
    if (is_chain) {
      asm volatile("setmaxnreg.dec.sync.aligned.u32 24;");
      if (warp == 8) chain_producer(sbase);
      bar_sync(11, 384);
      asm volatile("setmaxnreg.inc.sync.aligned.u32 40;");
    } else {
      asm volatile("setmaxnreg.dec.sync.aligned.u32 40;");
    }
    if (warp == 8) {
      if (is_kv) { if (tid == 256) kv_producer(p, sbase, kvb); __syncwarp(); bar_sync(2, 288); }
      if (tid == 256) bulk_producer(p, sbase);
      __syncwarp();
    } else if (warp < 11) flag_helper(sbase, warp - 9);
  } else {
    if (is_chain) {
      asm volatile("setmaxnreg.inc.sync.aligned.u32 240;");
      chain_consumer(p, sm, sbase);
      fence_proxy_async_smem();
      asm volatile("setmaxnreg.dec.sync.aligned.u32 232;");
      bar_sync(11, 384);
    } else {
      asm volatile("setmaxnreg.inc.sync.aligned.u32 232;");
    }
    Stg sg{1};
    if (is_kv) {
      kv_consumer(p, sg, sbase, kvb);
      fence_proxy_async_smem();
      bar_sync(2, 288);
    }
    bulk_consumer(p, sg, sbase);
    post_flag(sg, sbase, 0xffffffffu, tid);
  }
  __syncthreads();
  if (tid == 0 && expired(bb)) g_err = 1;
  if (p.do_reset) {
    if (tid == 0) { __threadfence(); sts32(bb + BR_MISC, atomicAdd(&g_f.exit_ctr, 1u)); }
    __syncthreads();
    if (lds32(bb + BR_MISC) == gridDim.x - 1) {
#pragma unroll 1
      for (int i = tid; i < (int)(sizeof(Flags) / 4); i += 384) ((uint32_t*)&g_f)[i] = 0;
    }
  }
}

typedef CUresult (*EncFn)(CUtensorMap*, CUtensorMapDataType, cuuint32_t, void*, const cuuint64_t*, const cuuint64_t*, const cuuint32_t*, const cuuint32_t*,
                          CUtensorMapInterleave, CUtensorMapSwizzle, CUtensorMapL2promotion, CUtensorMapFloatOOBfill);
static void make_map(EncFn enc, CUtensorMap* m, const void* base, uint64_t inner, uint64_t outer, uint32_t box_in, uint32_t box_out) {
  cuuint64_t dims[2] = {inner, outer}; cuuint64_t strides[1] = {inner * 2};
  cuuint32_t box[2] = {box_in, box_out}; cuuint32_t es[2] = {1, 1};
  enc(m, CU_TENSOR_MAP_DATA_TYPE_BFLOAT16, 2, (void*)base, dims, strides, box, es, CU_TENSOR_MAP_INTERLEAVE_NONE, CU_TENSOR_MAP_SWIZZLE_128B,
      CU_TENSOR_MAP_L2_PROMOTION_L2_256B, CU_TENSOR_MAP_FLOAT_OOB_FILL_NONE);
}
static void make_map3(EncFn enc, CUtensorMap* m, const void* base, uint64_t inner, uint64_t outer, uint32_t box_rows, uint32_t box_slabs) {
  cuuint64_t dims[3] = {64, outer, inner / 64}; cuuint64_t strides[2] = {inner * 2, 128};
  cuuint32_t box[3] = {64, box_rows, box_slabs}; cuuint32_t es[3] = {1, 1, 1};
  enc(m, CU_TENSOR_MAP_DATA_TYPE_BFLOAT16, 3, (void*)base, dims, strides, box, es, CU_TENSOR_MAP_INTERLEAVE_NONE, CU_TENSOR_MAP_SWIZZLE_128B,
      CU_TENSOR_MAP_L2_PROMOTION_L2_256B, CU_TENSOR_MAP_FLOAT_OOB_FILL_NONE);
}
#define DG0 1100
#define DG20 2500
static void fill_params(Params& p, void* const* d_in, void* d_out) {
  static EncFn enc = nullptr;
  if (!enc) {
    void* fn = nullptr; cudaDriverEntryPointQueryResult qr;
    cudaGetDriverEntryPoint("cuTensorMapEncodeTiled", &fn, cudaEnableDefault, &qr);
    enc = (EncFn)fn;
    cudaFuncSetAttribute(mega_kernel, cudaFuncAttributeMaxDynamicSharedMemorySize, SMEM_TOTAL);
  }
  void *kv, *kvm, *o, *kt, *yt;
  cudaGetSymbolAddress(&kt, g_kvT); cudaGetSymbolAddress(&yt, g_ybT);
  cudaGetSymbolAddress(&kv, g_KV); cudaGetSymbolAddress(&kvm, g_KVm); cudaGetSymbolAddress(&o, g_O);
  p.x = (const bf16*)d_in[0]; p.mem0 = (const bf16*)d_in[1]; p.Wq = (const bf16*)d_in[2]; p.Wk = (const bf16*)d_in[3];
  p.Wv = (const bf16*)d_in[4]; p.Wo = (const bf16*)d_in[5];
  p.bk = (const bf16*)d_in[8]; p.bv = (const bf16*)d_in[9]; p.shift_k = (const bf16*)d_in[10]; p.ssm_k = (const bf16*)d_in[11];
  p.ssm_D = (const bf16*)d_in[12]; p.gate_w = (const bf16*)d_in[13];
  p.out = (bf16*)d_out;
  make_map(enc, &p.tmX, p.x, DM, SEQ, 64, 128);
  make_map(enc, &p.tmO, o, HD, SEQ, 64, 64);
  make_map(enc, &p.tmOl, o, HD, SEQ, 64, 128);
  make_map(enc, &p.tmKV, kv, HD, 2 * SEQ, 64, 64);
  make_map3(enc, &p.tmKVl, kv, HD, 2 * SEQ, 128, 2);
  make_map3(enc, &p.tmKVm, kvm, HD, 2 * NSEG * NM, 32, 2);
  make_map3(enc, &p.tmWq, p.Wq, HD, DM, 64, 4);
  make_map3(enc, &p.tmWk, p.Wk, HD, DM, 64, 2);
  make_map3(enc, &p.tmWv, p.Wv, HD, DM, 64, 2);
  make_map3(enc, &p.tmWo, p.Wo, DM, HD, 64, 5);
  make_map3(enc, &p.tmWo2, p.Wo, DM, HD, 64, 2);
  make_map(enc, &p.tmW1[0], p.Wq, HD, DM, 64, 64);
  make_map(enc, &p.tmW1[1], p.Wk, HD, DM, 64, 64);
  make_map(enc, &p.tmW1[2], p.Wv, HD, DM, 64, 64);
  make_map(enc, &p.tmWo1, p.Wo, DM, HD, 64, 128);
  make_map(enc, &p.tmKT, kt, 64, DM * 32, 64, 32);
  make_map(enc, &p.tmYT, yt, 64, DM * 32, 64, 32);
  p.dG = DG0; p.dG2 = DG20;
  p.t_begin = 0; p.t_end = N_TASKS; p.do_chain = 1; p.do_reset = 1; p.do_kv = 1;
}

static void launch_staged(const Params& p, int grid) {
  void* fl; cudaGetSymbolAddress(&fl, g_f);
  Params q = p; q.do_reset = 0;
  cudaMemsetAsync(fl, 0, sizeof(Flags), cudaStreamPerThread);
  q.do_chain = 0; q.do_kv = 1; q.t_begin = 0; q.t_end = T_CONV; mega_kernel<<<132, 384, SMEM_TOTAL>>>(q);
  cudaMemsetAsync(fl, 0, 4, cudaStreamPerThread);
  q.do_chain = 1; q.do_kv = 0; q.t_begin = T_CONV; q.t_end = T_QA0; mega_kernel<<<grid, 384, SMEM_TOTAL>>>(q);
  cudaMemsetAsync(fl, 0, 4, cudaStreamPerThread);
  q.do_chain = 0; q.do_kv = 0; q.t_begin = T_QA0; q.t_end = N_TASKS; mega_kernel<<<grid, 384, SMEM_TOTAL>>>(q);
  cudaMemsetAsync(fl, 0, sizeof(Flags), cudaStreamPerThread);
}

extern "C" void kernel_launch(void* const* d_in, const int* in_sizes, int n_in, void* d_out, int out_size) {
  Params p;
  fill_params(p, d_in, d_out);
  static int max_clusters = -1;
  if (max_clusters < 0) {
    cudaLaunchConfig_t cfg = {}; cfg.gridDim = dim3(132); cfg.blockDim = dim3(384); cfg.dynamicSmemBytes = SMEM_TOTAL;
    cudaLaunchAttribute at[1]; at[0].id = cudaLaunchAttributeClusterDimension; at[0].val.clusterDim.x = 2; at[0].val.clusterDim.y = 1; at[0].val.clusterDim.z = 1;
    cfg.attrs = at; cfg.numAttrs = 1;
    int n = 0;
    if (cudaOccupancyMaxActiveClusters(&n, mega_kernel, &cfg) != cudaSuccess) { (void)cudaGetLastError(); n = 66; }
    max_clusters = n;
  }
  if (max_clusters >= 66) mega_kernel<<<132, 384, SMEM_TOTAL>>>(p);
  else launch_staged(p, 2 * max_clusters);
}
```
